```python
import torch

def _softmax(x, axis=-1):
    return torch.softmax(x, dim=axis)
def _gelu(x):
    return torch.nn.functional.gelu(x, approximate="tanh")
def _silu(x):
    return torch.nn.functional.silu(x)
def _sigmoid(x):
    return torch.sigmoid(x)
def _layernorm(x, axis=-1, eps=1e-5):
    m = x.mean(dim=axis, keepdim=True)
    v = x.var(dim=axis, keepdim=True, unbiased=False)
    return (x - m) / torch.sqrt(v + eps)
def _scatter_add(tgt, idx, src, axis=0):
    return tgt.clone().index_add_(axis, idx, src)
def _segment_sum(src, seg, n):
    out = torch.zeros((n,) + src.shape[1:], dtype=src.dtype)
    return out.index_add_(0, seg, src)
def _pad(x, pw):
    flat = tuple(v for pair in reversed(pw) for v in pair)
    return torch.nn.functional.pad(x, flat)

kernel_name = 'parallel_sum__softmax_full_mha__moe_arch_mod__prompt'

def setup_inputs():

    _w = (lambda a: (lambda t: t.to(torch.bfloat16) if t.is_floating_point() else t)(torch.as_tensor(a)))
    def _A_setup():
        B, S, D = 1, 2048, 640
        return {
            "x": _w((lambda *s: torch.randn(*s, dtype=torch.bfloat16) * 0.05)(B, S, D)),
            "wqkv": _w((lambda *s: torch.randn(*s, dtype=torch.bfloat16) * 0.2)(D, 3 * D)),
            "wo": _w((lambda *s: torch.randn(*s, dtype=torch.bfloat16) * 0.2)(D, D)),
        }
    _A_in = _A_setup()

    def _B_setup():
        B, S, D, F, C = 1, 2048, 640, 1728, 2
        return {
            "x": _w((lambda *s: torch.randn(*s, dtype=torch.bfloat16) * 0.05)(B, S, D)),
            "w_r": _w((lambda *s: torch.randn(*s, dtype=torch.bfloat16) * 0.8)(D)),
            "w_gate": _w((lambda *s: torch.randn(*s, dtype=torch.bfloat16) * 0.2)(D, F)),
            "w_up": _w((lambda *s: torch.randn(*s, dtype=torch.bfloat16) * 0.2)(D, F)),
            "w_down": _w((lambda *s: torch.randn(*s, dtype=torch.bfloat16) * 0.2)(F, D)),
        }
    _B_in = _B_setup()

    return {
        "A_x": _A_in["x"],
        "A_wqkv": _A_in["wqkv"],
        "A_wo": _A_in["wo"],
        "B_x": _B_in["x"],
        "B_w_r": _B_in["w_r"],
        "B_w_gate": _B_in["w_gate"],
        "B_w_up": _B_in["w_up"],
        "B_w_down": _B_in["w_down"],
    }

def reference(A_x, A_wqkv, A_wo, B_x, B_w_r, B_w_gate, B_w_up, B_w_down):
    def _A_ref(x, wqkv, wo):
        B, S, D = x.shape
        H = 32; Dh = D // H
        qkv = (lambda x, *d: x.permute(*d))((x @ wqkv).reshape(B, S, 3, H, Dh), 2, 0, 3, 1, 4)
        q, k, v = qkv[0], qkv[1], qkv[2]
        scale = Dh ** -0.5
        scores = torch.einsum("bhqd,bhkd->bhqk", q, k) * scale
        p = _softmax(scores, axis=-1)
        o = torch.einsum("bhqk,bhkd->bhqd", p, v)
        return (lambda x, *d: x.permute(*d))(o, 0, 2, 1, 3).reshape(B, S, D) @ wo

    def _B_ref(x, w_r, w_gate, w_up, w_down):
        B, S, D = x.shape
        C = 2
        r = x @ w_r
        idx = torch.argsort(-r, axis=-1)[:, :C]
        idx_e = (lambda x, n, axis: torch.repeat_interleave(x, n, dim=axis))(idx.reshape(B, C, 1), D, axis=2)
        x_sel = (lambda x, i, axis: torch.take_along_dim(x, i, dim=axis))(x, idx_e, axis=1)
        g = _silu(x_sel @ w_gate)
        u = x_sel @ w_up
        y = (g * u) @ w_down
        r_sel = _sigmoid((lambda x, i, axis: torch.take_along_dim(x, i, dim=axis))(r, idx, axis=1))
        y = y * r_sel.reshape(B, C, 1)
        b_off = (torch.arange(B) * S).reshape(B, 1)
        flat_idx = (idx + b_off).reshape(B * C)
        zero = (x * 0.0).reshape(B * S, D)
        upd = _scatter_add(zero, flat_idx, y.reshape(B * C, D), axis=0)
        return x + upd.reshape(B, S, D)

    x = A_x
    xn = _layernorm(x, axis=-1)
    return x + _A_ref(xn, A_wqkv, A_wo) + _B_ref(xn, B_w_r, B_w_gate, B_w_up, B_w_down)
```

```cpp
#include <cuda_runtime.h>
#include <cuda_bf16.h>
#include <cuda.h>
#include <stdint.h>

namespace {

constexpr int S_ = 2048, D_ = 640, H_ = 32, F_ = 1728;

constexpr int HEAD_ELEMS = 256 * 192;
constexpr int HEAD_BYTES = HEAD_ELEMS * 2;
__device__ __align__(1024) __nv_bfloat16 g_o[S_ * D_];
__device__ __align__(1024) __nv_bfloat16 g_qkv[3 * H_ * HEAD_ELEMS];
__device__ __align__(1024) __nv_bfloat16 g_wot[D_ * D_];
__device__ unsigned long long g_rp[S_];
__device__ unsigned long long g_stat[S_];
__device__ unsigned long long g_cs[16 * 3 * D_];
__device__ float g_ypart[4 * 2 * D_];
__device__ uint32_t g_upd[D_];
__device__ int g_idx[2];
__device__ float2 g_statp[S_];
__device__ unsigned g_ffn_done;

constexpr unsigned POLY_PAT = 0xADu;

#define TL(k, i) do {} while (0)

__device__ __forceinline__ uint32_t s2u(const void* p) { return (uint32_t)__cvta_generic_to_shared(p); }
__device__ __forceinline__ void mbar_init(uint32_t bar, uint32_t cnt) {
  asm volatile("mbarrier.init.shared::cta.b64 [%0], %1;" ::"r"(bar), "r"(cnt) : "memory");
}
__device__ __forceinline__ void mbar_expect_tx(uint32_t bar, uint32_t bytes) {
  asm volatile("mbarrier.arrive.expect_tx.shared::cta.b64 _, [%0], %1;" ::"r"(bar), "r"(bytes) : "memory");
}
__device__ __forceinline__ void mbar_arrive(uint32_t bar) {
  asm volatile("mbarrier.arrive.shared::cta.b64 _, [%0];" ::"r"(bar) : "memory");
}
__device__ __forceinline__ bool mbar_try(uint32_t bar, uint32_t parity) {
  uint32_t ok;
  asm volatile("{\n.reg .pred p;\nmbarrier.try_wait.parity.shared::cta.b64 p, [%1], %2;\nselp.u32 %0, 1, 0, p;\n}"
               : "=r"(ok) : "r"(bar), "r"(parity) : "memory");
  return ok != 0;
}
__device__ __forceinline__ void mbar_wait(uint32_t bar, uint32_t parity) {
  if (mbar_try(bar, parity)) return;
  for (int it = 0; !mbar_try(bar, parity); ++it)
    if (it > (1 << 22)) __trap();
}
__device__ __forceinline__ void bulk_g2s(uint32_t dst, const void* src, uint32_t bytes, uint32_t bar) {
  asm volatile("cp.async.bulk.shared::cluster.global.mbarrier::complete_tx::bytes [%0], [%1], %2, [%3];"
               ::"r"(dst), "l"(src), "r"(bytes), "r"(bar) : "memory");
}
__device__ __forceinline__ void tma2d(uint32_t dst, const CUtensorMap* map, int c0, int c1, uint32_t bar) {
  asm volatile("cp.async.bulk.tensor.2d.shared::cluster.global.mbarrier::complete_tx::bytes [%0], [%1, {%3, %4}], [%2];"
               ::"r"(dst), "l"(map), "r"(bar), "r"(c0), "r"(c1) : "memory");
}
__device__ __forceinline__ void prefetch_l2(const void* p, uint32_t bytes) {
  asm volatile("cp.async.bulk.prefetch.L2.global [%0], %1;" ::"l"(p), "r"(bytes) : "memory");
}
__device__ __forceinline__ void pdl_launch() { asm volatile("griddepcontrol.launch_dependents;" ::: "memory"); }
__device__ __forceinline__ void pdl_wait() { asm volatile("griddepcontrol.wait;" ::: "memory"); }
__device__ __forceinline__ void fence_async_smem() { asm volatile("fence.proxy.async.shared::cta;" ::: "memory"); }
__device__ __forceinline__ void bar_sync(int id, int n) { asm volatile("bar.sync %0, %1;" ::"r"(id), "r"(n) : "memory"); }
constexpr uint32_t tag = 1;
__device__ __forceinline__ void put_packet(unsigned long long* p, uint32_t payload, uint32_t tag_) {
  asm volatile("st.relaxed.gpu.global.b64 [%0], %1;" ::"l"(p), "l"(((unsigned long long)tag_ << 32) | payload) : "memory");
}
__device__ __forceinline__ unsigned long long ld_packet(const unsigned long long* p) {
  unsigned long long v;
  asm volatile("ld.relaxed.gpu.global.b64 %0, [%1];" : "=l"(v) : "l"(p) : "memory");
  return v;
}
__device__ __forceinline__ uint32_t get_packet(const unsigned long long* p, uint32_t tag_) {
  unsigned long long v = ld_packet(p);
  for (int it = 0; (uint32_t)(v >> 32) != tag_; ++it) {
    if (it > (1 << 22)) __trap();
    v = ld_packet(p);
  }
  return (uint32_t)v;
}

#define WG_FENCE() asm volatile("wgmma.fence.sync.aligned;" ::: "memory")
#define WG_COMMIT() asm volatile("wgmma.commit_group.sync.aligned;" ::: "memory")
template <int N> __device__ __forceinline__ void wg_wait() {
  asm volatile("wgmma.wait_group.sync.aligned %0;" ::"n"(N) : "memory");
}
template <int N> __device__ __forceinline__ void pin(float (&d)[N]) {
#pragma unroll
  for (int i = 0; i < N; i++) asm volatile("" : "+f"(d[i])::"memory");
}
template <int N> __device__ __forceinline__ void pin(uint32_t (&d)[N]) {
#pragma unroll
  for (int i = 0; i < N; i++) asm volatile("" : "+r"(d[i])::"memory");
}
__device__ __forceinline__ uint64_t mkdesc(uint32_t addr, uint32_t lbo, uint32_t sbo, uint32_t swz) {
  return (uint64_t)((addr & 0x3FFFF) >> 4) | ((uint64_t)(lbo >> 4) << 16) | ((uint64_t)(sbo >> 4) << 32) |
         ((uint64_t)swz << 62);
}

#define R4(d, i) "+f"(d[i]), "+f"(d[i + 1]), "+f"(d[i + 2]), "+f"(d[i + 3])
#define R8(d, i) R4(d, i), R4(d, i + 4)
#define R16(d, i) R8(d, i), R8(d, i + 8)
#define R32(d, i) R16(d, i), R16(d, i + 16)

template <int ACC> __device__ __forceinline__ void mma_ss64(float (&d)[32], uint64_t da, uint64_t db) {
  asm volatile(
      "wgmma.mma_async.sync.aligned.m64n64k16.f32.bf16.bf16 "
      "{%0,%1,%2,%3,%4,%5,%6,%7,%8,%9,%10,%11,%12,%13,%14,%15,%16,%17,%18,%19,%20,%21,%22,%23,%24,%25,%26,%27,%28,%29,%30,%31},"
      "%32, %33, %34, 1, 1, 0, 0;"
      : R32(d, 0) : "l"(da), "l"(db), "n"(ACC));
}
__device__ __forceinline__ void mma_pv(float (&d)[12], uint32_t a0, uint32_t a1, uint32_t a2, uint32_t a3, uint64_t db) {
  asm volatile(
      "wgmma.mma_async.sync.aligned.m64n24k16.f32.bf16.bf16 "
      "{%0,%1,%2,%3,%4,%5,%6,%7,%8,%9,%10,%11}, {%12,%13,%14,%15}, %16, 1, 1, 1, 1;"
      : R8(d, 0), R4(d, 8) : "r"(a0), "r"(a1), "r"(a2), "r"(a3), "l"(db));
}
__device__ __forceinline__ void mma_ss240(float (&d)[120], uint64_t da, uint64_t db, int acc) {
  asm volatile(
      "{\n.reg .pred p;\nsetp.ne.b32 p, %122, 0;\n"
      "wgmma.mma_async.sync.aligned.m64n240k16.f32.bf16.bf16 "
      "{%0,%1,%2,%3,%4,%5,%6,%7,%8,%9,%10,%11,%12,%13,%14,%15,%16,%17,%18,%19,%20,%21,%22,%23,%24,%25,%26,%27,%28,%29,"
      "%30,%31,%32,%33,%34,%35,%36,%37,%38,%39,%40,%41,%42,%43,%44,%45,%46,%47,%48,%49,%50,%51,%52,%53,%54,%55,%56,%57,%58,%59,"
      "%60,%61,%62,%63,%64,%65,%66,%67,%68,%69,%70,%71,%72,%73,%74,%75,%76,%77,%78,%79,%80,%81,%82,%83,%84,%85,%86,%87,%88,%89,"
      "%90,%91,%92,%93,%94,%95,%96,%97,%98,%99,%100,%101,%102,%103,%104,%105,%106,%107,%108,%109,%110,%111,%112,%113,%114,%115,%116,%117,%118,%119},"
      "%120, %121, p, 1, 1, 0, 1;\n}"
      : R32(d, 0), R32(d, 32), R32(d, 64), R16(d, 96), R8(d, 112)
      : "l"(da), "l"(db), "r"(acc));
}
__device__ __forceinline__ void mma_ss80(float (&d)[40], uint64_t da, uint64_t db, int acc) {
  asm volatile(
      "{\n.reg .pred p;\nsetp.ne.b32 p, %42, 0;\n"
      "wgmma.mma_async.sync.aligned.m64n80k16.f32.bf16.bf16 "
      "{%0,%1,%2,%3,%4,%5,%6,%7,%8,%9,%10,%11,%12,%13,%14,%15,%16,%17,%18,%19,%20,%21,%22,%23,%24,%25,%26,%27,%28,%29,"
      "%30,%31,%32,%33,%34,%35,%36,%37,%38,%39},"
      "%40, %41, p, 1, 1, 0, 1;\n}"
      : R32(d, 0), R8(d, 32)
      : "l"(da), "l"(db), "r"(acc));
}

__device__ __forceinline__ void sts_if(bool p, uint32_t addr, uint32_t v) {
  asm volatile("{\n.reg .pred p;\nsetp.ne.u32 p, %2, 0;\n@p st.shared.b32 [%0], %1;\n}" ::"r"(addr), "r"(v), "r"((uint32_t)p));
}
__device__ __forceinline__ float bf_round(float v) {
  uint32_t r;
  asm("cvt.rn.bf16x2.f32 %0, %1, %2;" : "=r"(r) : "f"(v), "f"(0.0f));
  return __uint_as_float(r);
}
__device__ __forceinline__ uint32_t pack_bf(float lo, float hi) {
  uint32_t r;
  asm("cvt.rn.bf16x2.f32 %0, %1, %2;" : "=r"(r) : "f"(hi), "f"(lo));
  return r;
}
__device__ __forceinline__ uint32_t bf2_add(uint32_t a, uint32_t b) {
  uint32_t r;
  asm("add.rn.bf16x2 %0, %1, %2;" : "=r"(r) : "r"(a), "r"(b));
  return r;
}
__device__ __forceinline__ uint32_t bf2_sub(uint32_t a, uint32_t b) {
  uint32_t r;
  asm("sub.rn.bf16x2 %0, %1, %2;" : "=r"(r) : "r"(a), "r"(b));
  return r;
}
__device__ __forceinline__ float bf_lo(uint32_t u) { return __uint_as_float(u << 16); }
__device__ __forceinline__ float bf_hi(uint32_t u) { return __uint_as_float(u & 0xFFFF0000u); }

#define K1_MC 0
constexpr int K1_THREADS = 384;
constexpr int K1_STAGES = 4;
constexpr int K1_A_BYTES = 128 * 64 * 2, K1_B_BYTES = 4 * 64 * 64 * 2, K1_STAGE = K1_A_BYTES + K1_B_BYTES;
constexpr int K1_AUX = K1_STAGES * K1_STAGE, K1_XROWS = K1_AUX + 128 + 1024 + 1024 + 3072;
constexpr int K1_SMEM = K1_XROWS + 16 * D_ * 2 + D_ * 2 + 1024;

__device__ __forceinline__ void tma2d_mc(uint32_t dst, const CUtensorMap* map, int c0, int c1, uint32_t bar) {
  asm volatile("cp.async.bulk.tensor.2d.shared::cluster.global.mbarrier::complete_tx::bytes.multicast::cluster "
               "[%0], [%1, {%3, %4}], [%2], %5;"
               ::"r"(dst), "l"(map), "r"(bar), "r"(c0), "r"(c1), "h"((uint16_t)3) : "memory");
}

__device__ __forceinline__ void ln_stats2(const uint2* __restrict__ rowp, const uint2* __restrict__ wrp, int row, int lane) {
  float s[2] = {0.f, 0.f}, q[2] = {0.f, 0.f}, tw[2] = {0.f, 0.f}, x0[2], sw = 0.f;
  x0[0] = bf_lo(rowp[0].x);
  x0[1] = bf_lo(rowp[D_ / 4].x);
#pragma unroll
  for (int i = 0; i < 5; i++) {
    const uint2 w = wrp[i * 32 + lane];
    const float w0 = bf_lo(w.x), w1 = bf_hi(w.x), w2 = bf_lo(w.y), w3 = bf_hi(w.y);
    sw += (w0 + w1) + (w2 + w3);
#pragma unroll
    for (int r = 0; r < 2; r++) {
      const uint2 u = rowp[r * (D_ / 4) + i * 32 + lane];
      const float d0 = bf_lo(u.x) - x0[r], d1 = bf_hi(u.x) - x0[r], d2 = bf_lo(u.y) - x0[r], d3 = bf_hi(u.y) - x0[r];
      s[r] += (d0 + d1) + (d2 + d3);
      q[r] = fmaf(d0, d0, fmaf(d1, d1, fmaf(d2, d2, fmaf(d3, d3, q[r]))));
      tw[r] = fmaf(d0, w0, fmaf(d1, w1, fmaf(d2, w2, fmaf(d3, w3, tw[r]))));
    }
  }
#pragma unroll
  for (int o = 16; o; o >>= 1) {
    s[0] += __shfl_xor_sync(~0u, s[0], o); q[0] += __shfl_xor_sync(~0u, q[0], o); tw[0] += __shfl_xor_sync(~0u, tw[0], o);
    s[1] += __shfl_xor_sync(~0u, s[1], o); q[1] += __shfl_xor_sync(~0u, q[1], o); tw[1] += __shfl_xor_sync(~0u, tw[1], o);
    sw += __shfl_xor_sync(~0u, sw, o);
  }
  const bool second = lane & 1;
  const float xs = second ? x0[1] : x0[0];
  const float md = (second ? s[1] : s[0]) * (1.0f / D_);
  const float var = fmaxf(fmaf(-md, md, (second ? q[1] : q[0]) * (1.0f / D_)), 0.f);
  const float m = bf_round(md + xs);
  const float den = bf_round(__fsqrt_rn(bf_round(bf_round(var) + 1e-5f)));
  if (lane < 2) {
    const uint32_t pay = __float_as_uint(m) | (__float_as_uint(den) >> 16);
    put_packet(&g_stat[row + lane], pay, tag);
    g_statp[row + lane] = make_float2(m, __fdiv_rn(1.0f, den));
    const float r = __fdiv_rn(fmaf(xs - m, sw, second ? tw[1] : tw[0]), den);
    put_packet(&g_rp[row + lane], __float_as_uint(bf_round(r)), tag);
  }
}

__device__ __forceinline__ void k1_store_duty(uint32_t sbase, int warp, int lane, int mb, int nb) {
#pragma unroll 1
  for (int ev = 0; ev < 6; ev++) {
    bar_sync(3 + ev, 256);
    if (lane == 0) {
      const int hl = 4 * (ev >> 1) + (warp - 8), wg = ev & 1;
      uint8_t* dst = reinterpret_cast<uint8_t*>(g_qkv) + (size_t)(nb * 12 + hl) * HEAD_BYTES + mb * 6144 + wg * 3072;
      asm volatile("cp.async.bulk.global.shared::cta.bulk_group [%0], [%1], 3072;"
                   ::"l"(dst), "r"(sbase + hl * 6144 + wg * 3072) : "memory");
      asm volatile("cp.async.bulk.commit_group;" ::: "memory");
    }
  }
  if (lane == 0) asm volatile("cp.async.bulk.wait_group.read 0;" ::: "memory");
}

__global__ void __launch_bounds__(K1_THREADS, 1)
k1_ln_qkv(const __grid_constant__ CUtensorMap map_x, const __grid_constant__ CUtensorMap map_w,
          const __nv_bfloat16* __restrict__ x, const __nv_bfloat16* __restrict__ wqkv,
          const __nv_bfloat16* __restrict__ w_r, const __nv_bfloat16* __restrict__ wo,
          const __nv_bfloat16* __restrict__ w_gate, const __nv_bfloat16* __restrict__ w_up,
          const __nv_bfloat16* __restrict__ w_down) {
  extern __shared__ uint8_t smem_raw[];
  const int tid = threadIdx.x, warp = __shfl_sync(0xffffffffu, tid >> 5, 0), lane = tid & 31;
  const int bid = blockIdx.x;
  if (tid == 0) TL(0, 0);
  uint8_t* smem = smem_raw + (((s2u(smem_raw) + 1023) & ~1023u) - s2u(smem_raw));
  const uint32_t sbase = s2u(smem);
  const uint32_t bar_full = sbase + K1_AUX, bar_empty = bar_full + 8 * K1_STAGES, bar_x = bar_empty + 8 * K1_STAGES;
  float2* s_stat = reinterpret_cast<float2*>(smem + K1_AUX + 128);
  float* s_cs = reinterpret_cast<float*>(smem + K1_AUX + 128 + 1024);
  const int mb = bid & 15, nb = bid >> 4, rank = bid & 1;

  if (tid == 256) {
    asm volatile("prefetch.tensormap [%0];" ::"l"(&map_x) : "memory");
    asm volatile("prefetch.tensormap [%0];" ::"l"(&map_w) : "memory");
    for (int s = 0; s < K1_STAGES; s++) { mbar_init(bar_full + 8 * s, 1); mbar_init(bar_empty + 8 * s, K1_MC ? 4 : 2); }
    mbar_init(bar_x, 1);
    asm volatile("fence.mbarrier_init.release.cluster;" ::: "memory");
  }
  __syncthreads();
  if (K1_MC) asm volatile("barrier.cluster.arrive.release.aligned;\nbarrier.cluster.wait.acquire.aligned;" ::: "memory");
  pdl_launch();

  if (warp == 8) {
    if (lane == 0) {
      mbar_expect_tx(bar_x, 16 * D_ * 2 + D_ * 2);
      bulk_g2s(sbase + K1_XROWS, x + (mb * 128 + nb * 16) * D_, 16 * D_ * 2, bar_x);
      bulk_g2s(sbase + K1_XROWS + 16 * D_ * 2, w_r, D_ * 2, bar_x);
      for (int kc = 0; kc < 10; kc++) {
        const int s = kc % K1_STAGES;
        if (kc >= K1_STAGES) mbar_wait(bar_empty + 8 * s, ((kc / K1_STAGES) - 1) & 1);
        mbar_expect_tx(bar_full + 8 * s, K1_STAGE);
        const uint32_t sa = sbase + s * K1_STAGE, sb = sa + K1_A_BYTES;
        tma2d(sa, &map_x, kc * 64, mb * 128, bar_full + 8 * s);
        for (int j = 0; j < 4; j++) tma2d(sb + j * 8192, &map_w, nb * 240 + 64 * j, kc * 64, bar_full + 8 * s);
      }
    }
    __syncwarp();
    k1_store_duty(sbase, warp, lane, mb, nb);
    return;
  }

  if (warp > 8) {
    const int at = tid - 288;
    float* s_part = reinterpret_cast<float*>(smem + K1_AUX + 128 + 2048);
    const uint2* s_x = reinterpret_cast<const uint2*>(smem + K1_XROWS);
    const int aw = warp - 9, rowb = mb * 128 + nb * 16;
    mbar_wait(bar_x, 0);
    if (at == 0) TL(0, 7);
    ln_stats2(s_x + aw * 2 * (D_ / 4), s_x + 16 * (D_ / 4), rowb + aw * 2, lane);
    {
      const int cv = at % 30, rg = at / 30;
      uint4 v[14];
      if (rg < 3) {
        const uint4* wp = reinterpret_cast<const uint4*>(wqkv + (size_t)(mb * 40 + rg) * (3 * D_) + nb * 240) + cv;
#pragma unroll
        for (int k = 0; k < 14; k++)
          v[k] = (rg + 3 * k < 40) ? __ldg(wp + (size_t)k * 3 * (3 * D_ / 8)) : make_uint4(0, 0, 0, 0);
      }
#pragma unroll 1
      for (int pr = aw + 3; pr < 8; pr += 3) ln_stats2(s_x + pr * 2 * (D_ / 4), s_x + 16 * (D_ / 4), rowb + pr * 2, lane);
      if (at == 0) TL(0, 6);
      if (rg < 3) {
        float c[8];
#pragma unroll
        for (int i = 0; i < 8; i++) c[i] = 0.f;
#pragma unroll
        for (int k = 0; k < 14; k++) {
          c[0] += bf_lo(v[k].x); c[1] += bf_hi(v[k].x); c[2] += bf_lo(v[k].y); c[3] += bf_hi(v[k].y);
          c[4] += bf_lo(v[k].z); c[5] += bf_hi(v[k].z); c[6] += bf_lo(v[k].w); c[7] += bf_hi(v[k].w);
        }
#pragma unroll
        for (int i = 0; i < 8; i++) s_part[rg * 240 + cv * 8 + i] = c[i];
      }
      bar_sync(1, 96);
      for (int c = at; c < 240; c += 96)
        put_packet(&g_cs[mb * (3 * D_) + nb * 240 + c], __float_as_uint(s_part[c] + s_part[240 + c] + s_part[480 + c]), tag);
    }
    if (at == 0) TL(0, 1);
    uint4 wov[5];
#pragma unroll
    for (int i = 0; i < 5; i++) {
      const int j = at + 96 * i;
      if (j < 400) wov[i] = __ldg(reinterpret_cast<const uint4*>(wo) + bid * 400 + j);
    }
    if (at < 9) {
      constexpr uint32_t CH = F_ * D_ * 2 / 384;
      const int c = bid * 3 + at % 3;
      const __nv_bfloat16* base = at < 3 ? w_gate : (at < 6 ? w_up : w_down);
      prefetch_l2(reinterpret_cast<const uint8_t*>(base) + (size_t)c * CH, CH);
    }
    {
      const unsigned long long* ps = &g_stat[mb * 128 + at];
      const unsigned long long* pc = &g_cs[nb * 240 + at];
      const int ncol = at < 48 ? 3 : 2;
      unsigned long long v0, v1, c[3][16];
      for (int it = 0;; ++it) {
        v0 = ld_packet(ps);
        v1 = at < 32 ? ld_packet(ps + 96) : (1ull << 32);
#pragma unroll
        for (int i = 0; i < 3; i++)
#pragma unroll
          for (int k = 0; k < 16; k++) c[i][k] = (i < ncol) ? ld_packet(pc + k * (3 * D_) + 96 * i) : (1ull << 32);
        uint32_t ok = (uint32_t)(v0 >> 32) & (uint32_t)(v1 >> 32);
#pragma unroll
        for (int i = 0; i < 3; i++)
#pragma unroll
          for (int k = 0; k < 16; k++) ok &= (uint32_t)(c[i][k] >> 32);
        if (ok == tag) break;
        if (it > (1 << 20)) __trap();
      }
      s_stat[at] = make_float2(__uint_as_float((uint32_t)v0 & 0xFFFF0000u), __fdiv_rn(1.0f, __uint_as_float((uint32_t)v0 << 16)));
      if (at < 32)
        s_stat[96 + at] = make_float2(__uint_as_float((uint32_t)v1 & 0xFFFF0000u), __fdiv_rn(1.0f, __uint_as_float((uint32_t)v1 << 16)));
#pragma unroll
      for (int i = 0; i < 3; i++) {
        float sum = 0.f;
#pragma unroll
        for (int k = 0; k < 16; k++) sum += __uint_as_float((uint32_t)c[i][k]);
        if (i < ncol) s_cs[at + 96 * i] = sum;
      }
    }
    __threadfence_block();
    asm volatile("bar.arrive 2, 352;" ::: "memory");
    if (at == 0) TL(0, 2);
#pragma unroll
    for (int i = 0; i < 5; i++) {
      const int j = at + 96 * i;
      if (j < 400) {
        const int li = bid * 400 + j, k = li / 80, cv = li % 80;
        const int dst = ((((cv / 10) * 10 + (k >> 6)) * 10 + (cv % 10)) * 8 + ((k >> 3) & 7)) * 8 + (k & 7);
        reinterpret_cast<uint4*>(g_wot)[dst] = wov[i];
      }
    }
    k1_store_duty(sbase, warp, lane, mb, nb);
    return;
  }

  const int wg = warp >> 2;
  float acc[120];
#pragma unroll
  for (int i = 0; i < 120; i++) acc[i] = 0.f;
  uint32_t peer_empty = 0;
  if (K1_MC) asm volatile("mapa.shared::cluster.u32 %0, %1, %2;" : "=r"(peer_empty) : "r"(bar_empty), "r"(rank ^ 1));
#pragma unroll 1
  for (int trip = 0; trip < 2; trip++) {
    const bool real = trip != 0;
    if (real) {
#pragma unroll 1
      for (int kc = 0; kc < 10; kc++) {
        const int s = kc % K1_STAGES;
        mbar_wait(bar_full + 8 * s, (kc / K1_STAGES) & 1);
        if (tid == 0 && kc == 0) TL(0, 3);
        const uint32_t sa = sbase + s * K1_STAGE + wg * 8192, sb = sbase + s * K1_STAGE + K1_A_BYTES;
        const uint64_t da = mkdesc(sa, 16, 1024, 1), db = mkdesc(sb, 8192, 1024, 1);
        WG_FENCE();
#pragma unroll
        for (int kk = 0; kk < 4; kk++) mma_ss240(acc, da + kk * 2, db + kk * 128, (kc | kk) != 0);
        WG_COMMIT();
        if (kc > 0) {
          wg_wait<1>();
          if ((tid & 127) == 0 && kc - 1 + K1_STAGES < 10) {
            const int sp = (kc - 1) % K1_STAGES;
            mbar_arrive(bar_empty + 8 * sp);
            if (K1_MC) asm volatile("mbarrier.arrive.release.cluster.shared::cluster.b64 _, [%0];" ::"r"(peer_empty + 8 * sp) : "memory");
          }
        }
      }
      wg_wait<0>();
      pin(acc);
      if (tid == 0) TL(0, 4);
      bar_sync(2, 352);
    }

    const int g = lane >> 2, t = lane & 3;
    const int rl = wg * 64 + (warp & 3) * 16 + g;
    const int grp = rl >> 3;
    const bool poly0 = (POLY_PAT >> (grp & 7)) & 1, poly1 = (POLY_PAT >> ((grp + 1) & 7)) & 1;
    const float qs = 0.22360679774997896f * 1.4426950408889634f * 5.421010862427522e-20f;
    const float kbig = 18446744073709551616.0f, ksmall = 3.308722450212111e-24f;
    const float2 st0 = s_stat[rl], st1 = s_stat[rl + 8];
    const float nm0 = -st0.x, nm1 = -st1.x;
    constexpr int HS = 1536;
    const uint32_t gb = sbase + (grp * 96 + g * 4) * 4;
    const float* const csp = s_cs + 2 * t;
#pragma unroll
    for (int bt = 0; bt < 3; bt++) {
      const int type = (nb * 12 + 4 * bt) >> 5;
      const bool isv = type == 2;
      const float s0 = st0.y * (type == 0 ? qs : (isv ? 1.0f : (poly0 ? ksmall : kbig)));
      const float s1 = st1.y * (type == 0 ? qs : (isv ? 1.0f : (poly1 ? ksmall : kbig)));
      const uint32_t hb = gb + 4 * bt * HS * 4;
      uint32_t p[5];
      p[0] = hb + 4 * t;
      p[1] = hb + 4 * ((t == 3 && !isv) ? 64 : 32 + t);
      p[2] = hb + 4 * (t < 2 ? 64 + t + (isv ? 0 : 1) : HS + t - 2);
      p[3] = hb + 4 * (t < 2 ? 2 + t : 30 + t);
      p[4] = hb + 4 * (t == 0 ? 34 : (isv ? (t == 1 ? 35 : 62 + t) : 63 + t));
      float2 csv[10];
#pragma unroll
      for (int jj = 0; jj < 10; jj++) csv[jj] = *reinterpret_cast<const float2*>(csp + 8 * (10 * bt + jj));
#pragma unroll
      for (int jj = 0; jj < 10; jj++) {
        const int j = 10 * bt + jj;
        const int h0 = (8 * jj) / 20;
        const float2 cs = csv[jj];
        const uint32_t q = p[jj % 5] + h0 * HS * 4;
        sts_if(real, q, pack_bf(fmaf(nm0, cs.x, acc[4 * j]) * s0, fmaf(nm0, cs.y, acc[4 * j + 1]) * s0));
        sts_if(real, q + 384, pack_bf(fmaf(nm1, cs.x, acc[4 * j + 2]) * s1, fmaf(nm1, cs.y, acc[4 * j + 3]) * s1));
      }
      const uint32_t cb = hb + t * HS * 4;
      const uint32_t a0 = type == 0 ? 0x00001F80u : (isv ? 0x00003F80u : (poly0 ? 0x00001E00u : 0u));
      const uint32_t a1 = type == 0 ? 0x00001F80u : (isv ? 0x00003F80u : (poly1 ? 0x00001E00u : 0u));
      const uint32_t b0 = type == 0 ? 0x1F800000u : (isv ? 0u : (poly0 ? 0x987E1880u : 0x64F05F80u));
      const uint32_t b1 = type == 0 ? 0x1F800000u : (isv ? 0u : (poly1 ? 0x987E1880u : 0x64F05F80u));
      sts_if(real, cb + (isv ? 66 : 35) * 4, a0); sts_if(real, cb + 384 + (isv ? 66 : 35) * 4, a1);
      sts_if(real, cb + 67 * 4, b0); sts_if(real, cb + 384 + 67 * 4, b1);
      if (real) {
        fence_async_smem();
        asm volatile("bar.arrive %0, 256;" ::"r"(3 + 2 * bt + wg) : "memory");
      }
    }
  }
  if (tid == 0) TL(0, 5);
}

constexpr int K2_THREADS = 512;
constexpr int K2_KV_BYTES = 98304, K2_Q_BYTES = 24576, K2_ZERO_BYTES = 2816;
constexpr int K2_SMEM = 2 * K2_KV_BYTES + K2_Q_BYTES + K2_ZERO_BYTES + 256;

__device__ __forceinline__ float ex2(float v) {
  float r;
  asm("ex2.approx.ftz.f32 %0, %1;" : "=f"(r) : "f"(v));
  return r;
}
__device__ __forceinline__ uint32_t exp_mufu(float a, float b) { return pack_bf(ex2(a), ex2(b)); }
__device__ __forceinline__ uint32_t exp_poly(float a, float b) {
  uint32_t w, t, p, r;
  asm("cvt.pack.sat.s16.s32 %0, %1, %2;" : "=r"(w) : "r"(__float_as_int(b)), "r"(__float_as_int(a)));
  const uint32_t u = w & 0x007F007Fu;
  asm("fma.rn.f16x2 %0, %1, %2, %3;" : "=r"(t) : "r"(u), "r"(0x79357935u), "r"(0x39593959u));
  asm("mul.rn.f16x2 %0, %1, %2;" : "=r"(p) : "r"(t), "r"(u));
  asm("lop3.b32 %0, %1, %2, %3, 0xEA;" : "=r"(r) : "r"(w), "r"(0xFF80FF80u), "r"(p));
  return r;
}
template <int BLO>
__device__ __forceinline__ void exp_half(const float (&s)[32], uint32_t (&p)[8]) {
#pragma unroll
  for (int b = BLO; b < BLO + 4; b++) {
    if ((POLY_PAT >> b) & 1) {
      p[2 * (b - BLO)] = exp_poly(s[4 * b], s[4 * b + 1]);
      p[2 * (b - BLO) + 1] = exp_poly(s[4 * b + 2], s[4 * b + 3]);
    } else {
      p[2 * (b - BLO)] = exp_mufu(s[4 * b], s[4 * b + 1]);
      p[2 * (b - BLO) + 1] = exp_mufu(s[4 * b + 2], s[4 * b + 3]);
    }
  }
}

__device__ __forceinline__ void mma16816(float (&c)[4], uint32_t a0, uint32_t a2, uint32_t b0, uint32_t b1) {
  asm volatile("mma.sync.aligned.m16n8k16.row.col.f32.bf16.bf16.f32 {%0,%1,%2,%3}, {%4,%5,%6,%5}, {%7,%8}, {%0,%1,%2,%3};"
               : "+f"(c[0]), "+f"(c[1]), "+f"(c[2]), "+f"(c[3]) : "r"(a0), "r"(0u), "r"(a2), "r"(b0), "r"(b1));
}
__device__ __forceinline__ void ldsm4t(uint32_t (&r)[4], uint32_t addr) {
  asm volatile("ldmatrix.sync.aligned.m8n8.x4.trans.shared.b16 {%0,%1,%2,%3}, [%4];"
               : "=r"(r[0]), "=r"(r[1]), "=r"(r[2]), "=r"(r[3]) : "r"(addr) : "memory");
}

constexpr int MOE_BOX = 128 * 128;
constexpr int MOE_SLOTS = 6, MOE_SLOT = 2 * MOE_BOX;

__device__ __noinline__ void moe_ffn(uint8_t* smem, int e, const __nv_bfloat16* __restrict__ x, const CUtensorMap* m_gate,
                                     const CUtensorMap* m_up, const CUtensorMap* m_down) {
  const int tid = threadIdx.x, lane = tid & 31, warp = __shfl_sync(0xffffffffu, tid >> 5, 0), g = lane >> 2, t = lane & 3;
  const uint32_t ring = (s2u(smem) + 1023) & ~1023u, bfull = ring + MOE_SLOTS * MOE_SLOT, bempty = bfull + 8 * MOE_SLOTS;
  __nv_bfloat16* xs = reinterpret_cast<__nv_bfloat16*>(smem + (ring - s2u(smem)) + MOE_SLOTS * MOE_SLOT + 128);
  __nv_bfloat16* hs = xs + 2 * D_;
  const int nblk = e == 3 ? 6 : 7, nchunk = e == 3 ? 3 : 4;
  const int nst1 = nblk * 5, nst = nst1 + nchunk * 5;
  __shared__ float s_val[16];
  __shared__ int s_idx[16];
  __shared__ int s_top[2];
  __shared__ float s_gate[2];
  __shared__ unsigned s_last;
  if (tid == 0) {
    for (int i = 0; i < MOE_SLOTS; i++) { mbar_init(bfull + 8 * i, 1); mbar_init(bempty + 8 * i, 8); }
    asm volatile("fence.mbarrier_init.release.cluster;" ::: "memory");
  }
  reinterpret_cast<uint32_t*>(hs)[tid] = 0u;
  __syncthreads();
  if (warp == 8) {
    if (lane == 0) {
      for (int st = 0; st < nst; st++) {
        const int sl = st % MOE_SLOTS;
        if (st >= MOE_SLOTS) mbar_wait(bempty + 8 * sl, ((st / MOE_SLOTS) - 1) & 1);
        const uint32_t slot = ring + sl * MOE_SLOT, bar = bfull + 8 * sl;
        mbar_expect_tx(bar, MOE_SLOT);
        if (st < nst1) {
          tma2d(slot, m_gate, (e * 7 + st / 5) * 64, (st % 5) * 128, bar);
          tma2d(slot + MOE_BOX, m_up, (e * 7 + st / 5) * 64, (st % 5) * 128, bar);
        } else {
          const int u = st - nst1;
          tma2d(slot, m_down, (u % 5) * 128, e * 448 + (u / 5) * 128, bar);
          tma2d(slot + MOE_BOX, m_down, (u % 5) * 128 + 64, e * 448 + (u / 5) * 128, bar);
        }
      }
    }
    __syncwarp();
  }

  if (warp < 8) {
    float rv[8];
    unsigned long long pk[8];
#pragma unroll
    for (int i = 0; i < 8; i++) pk[i] = ld_packet(&g_rp[tid + 256 * i]);
#pragma unroll
    for (int i = 0; i < 8; i++)
      rv[i] = __uint_as_float((uint32_t)(pk[i] >> 32) == tag ? (uint32_t)pk[i] : get_packet(&g_rp[tid + 256 * i], tag));
    if (tid == 0) TL(1, 1);
    int first = -1;
    for (int pass = 0; pass < 2; pass++) {
      float bv = -INFINITY; int bi = 0x7fffffff;
#pragma unroll
      for (int i = 0; i < 8; i++) {
        const int idx = tid + 256 * i;
        if (idx != first && (rv[i] > bv || (rv[i] == bv && idx < bi))) { bv = rv[i]; bi = idx; }
      }
#pragma unroll
      for (int o = 16; o; o >>= 1) {
        const float ov = __shfl_xor_sync(0xffffffffu, bv, o);
        const int oi = __shfl_xor_sync(0xffffffffu, bi, o);
        if (ov > bv || (ov == bv && oi < bi)) { bv = ov; bi = oi; }
      }
      if (lane == 0) { s_val[warp] = bv; s_idx[warp] = bi; }
      bar_sync(1, 256);
      if (warp == 0) {
        float v = s_val[lane & 7]; int ix = s_idx[lane & 7];
#pragma unroll
        for (int o = 4; o; o >>= 1) {
          const float ov = __shfl_xor_sync(0xffffffffu, v, o);
          const int oi = __shfl_xor_sync(0xffffffffu, ix, o);
          if (ov > v || (ov == v && oi < ix)) { v = ov; ix = oi; }
        }
        if (lane == 0) {
          if (ix < 0 || ix >= S_) ix = pass;
          s_top[pass] = ix;
          s_gate[pass] = bf_round(1.0f / (1.0f + __expf(-v)));
          if (e == 0) g_idx[pass] = ix;
        }
      }
      bar_sync(1, 256);
      first = s_top[0];
    }
    for (int i = tid; i < 2 * D_; i += 256) {
      const int tok = i / D_, d = i % D_;
      const uint32_t st = get_packet(&g_stat[s_top[tok]], tag);
      const float m = __uint_as_float(st & 0xFFFF0000u), rstd = __fdiv_rn(1.0f, __uint_as_float(st << 16));
      reinterpret_cast<uint16_t*>(xs)[i] =
          (uint16_t)(__float_as_uint(bf_round(bf_round(__bfloat162float(x[s_top[tok] * D_ + d]) - m) * rstd)) >> 16);
    }
    bar_sync(1, 256);
    if (tid == 0) TL(1, 2);

    const uint32_t* xs32 = reinterpret_cast<const uint32_t*>(xs);
    int st = 0;
#pragma unroll 1
    for (int blk = 0; blk < nblk; blk++) {
      float cg[4] = {0.f, 0.f, 0.f, 0.f}, cu[4] = {0.f, 0.f, 0.f, 0.f};
#pragma unroll 1
      for (int kc = 0; kc < 5; kc++, st++) {
        const int sl = st % MOE_SLOTS;
        mbar_wait(bfull + 8 * sl, (st / MOE_SLOTS) & 1);
        const uint32_t base = ring + sl * MOE_SLOT + (lane >> 4) * MOE_BOX + (lane & 15) * 128 + ((warp ^ (lane & 7)) << 4);
#pragma unroll
        for (int ks = 0; ks < 8; ks++) {
          const int kw = kc * 64 + ks * 8 + t;
          const uint32_t a0 = g < 2 ? xs32[g * (D_ / 2) + kw] : 0u, a2 = g < 2 ? xs32[g * (D_ / 2) + kw + 4] : 0u;
          uint32_t b[4];
          ldsm4t(b, base + ks * 2048);
          mma16816(cg, a0, a2, b[0], b[1]);
          mma16816(cu, a0, a2, b[2], b[3]);
        }
        __syncwarp();
        if (lane == 0) mbar_arrive(bempty + 8 * sl);
      }
      if (g < 2) {
        float h[2];
#pragma unroll
        for (int i = 0; i < 2; i++) {
          const float gb = bf_round(cg[i]), ub = bf_round(cu[i]);
          h[i] = bf_round(gb / (1.0f + __expf(-gb))) * ub;
        }
        reinterpret_cast<uint32_t*>(hs)[g * 256 + blk * 32 + warp * 4 + t] = pack_bf(h[0], h[1]);
      }
    }
    bar_sync(1, 256);
    if (tid == 0) TL(1, 3);

    float cd[5][2][4];
#pragma unroll
    for (int q = 0; q < 5; q++)
#pragma unroll
      for (int i = 0; i < 4; i++) { cd[q][0][i] = 0.f; cd[q][1][i] = 0.f; }
    const uint32_t* hs32 = reinterpret_cast<const uint32_t*>(hs);
#pragma unroll 1
    for (int fc = 0; fc < nchunk; fc++) {
#pragma unroll
      for (int q = 0; q < 5; q++, st++) {
        const int sl = st % MOE_SLOTS;
        mbar_wait(bfull + 8 * sl, (st / MOE_SLOTS) & 1);
        const uint32_t base = ring + sl * MOE_SLOT + (lane >> 4) * MOE_BOX + (lane & 15) * 128 + ((warp ^ (lane & 7)) << 4);
#pragma unroll
        for (int ks = 0; ks < 8; ks++) {
          const int kw = fc * 64 + ks * 8 + t;
          const uint32_t a0 = g < 2 ? hs32[g * 256 + kw] : 0u, a2 = g < 2 ? hs32[g * 256 + kw + 4] : 0u;
          uint32_t b[4];
          ldsm4t(b, base + ks * 2048);
          mma16816(cd[q][0], a0, a2, b[0], b[1]);
          mma16816(cd[q][1], a0, a2, b[2], b[3]);
        }
        __syncwarp();
        if (lane == 0) mbar_arrive(bempty + 8 * sl);
      }
    }
    if (g < 2) {
#pragma unroll
      for (int q = 0; q < 5; q++)
#pragma unroll
        for (int b = 0; b < 2; b++)
          *reinterpret_cast<float2*>(&g_ypart[(e * 2 + g) * D_ + q * 128 + b * 64 + warp * 8 + 2 * t]) =
              make_float2(cd[q][b][0], cd[q][b][1]);
    }
  }
  __threadfence();
  __syncthreads();
  if (tid == 0) s_last = atomicAdd(&g_ffn_done, 1u) & 3u;
  __syncthreads();
  if (s_last == 3) {
    __threadfence();
    for (int i = tid; i < D_; i += K2_THREADS) {
      const int tok = i / (D_ / 2), d = 2 * (i % (D_ / 2));
      float s0 = 0.f, s1 = 0.f;
#pragma unroll
      for (int k = 0; k < 4; k++) {
        const float2 v = __ldcg(reinterpret_cast<const float2*>(&g_ypart[(k * 2 + tok) * D_ + d]));
        s0 += v.x; s1 += v.y;
      }
      g_upd[i] = pack_bf(bf_round(s0) * s_gate[tok], bf_round(s1) * s_gate[tok]);
    }
  }
}

__device__ __forceinline__ void attn_fallback(float (&o)[12], uint8_t* smem, uint32_t sK, uint32_t sV, uint32_t qoff, int wg,
                                              uint64_t dQ0, uint64_t dQ1) {
  const int tid = threadIdx.x & 127;
  uint16_t* q16 = reinterpret_cast<uint16_t*>(smem + qoff);
  for (int i = tid; i < 8 * 192; i += 128) {
    const int in = i % 192, slot = (in >> 6) * 8 + (in & 7);
    uint16_t* p = q16 + i;
    const bool cst = slot == 14 || slot == 15 || slot == 22 || slot == 23;
    const float v = cst ? 0.f : __uint_as_float((uint32_t)*p << 16) * 2361183241434822606848.0f;
    *p = (uint16_t)(__float_as_uint(v) >> 16);
  }
  fence_async_smem();
  bar_sync(1 + wg, 128);
  const uint64_t dK0 = mkdesc(sK, 128, 384, 0), dK1 = mkdesc(sK + 256, 0, 384, 0), dV = mkdesc(sV, 384, 128, 0);
  const float up = 2361183241434822606848.0f, down = 4.235164736271502e-22f;
  float m0 = -INFINITY, m1 = -INFINITY;
#pragma unroll
  for (int i = 0; i < 12; i++) o[i] = 0.f;
#pragma unroll 1
  for (int j = 0; j < 32; j++) {
    float s[32];
    uint32_t p[16];
    const uint64_t off = (uint64_t)(j * 192);
    WG_FENCE();
    mma_ss64<0>(s, dQ0, dK0 + off);
    mma_ss64<1>(s, dQ1, dK1 + off);
    WG_COMMIT();
    wg_wait<0>();
    pin(s);
    pin(o);
    float n0 = m0, n1 = m1;
#pragma unroll
    for (int b = 0; b < 8; b++) {
      const float f = ((POLY_PAT >> b) & 1) ? up : down;
      s[4 * b] *= f; s[4 * b + 1] *= f; s[4 * b + 2] *= f; s[4 * b + 3] *= f;
      n0 = fmaxf(n0, fmaxf(s[4 * b], s[4 * b + 1]));
      n1 = fmaxf(n1, fmaxf(s[4 * b + 2], s[4 * b + 3]));
    }
    n0 = fmaxf(n0, __shfl_xor_sync(0xffffffffu, n0, 1)); n0 = fmaxf(n0, __shfl_xor_sync(0xffffffffu, n0, 2));
    n1 = fmaxf(n1, __shfl_xor_sync(0xffffffffu, n1, 1)); n1 = fmaxf(n1, __shfl_xor_sync(0xffffffffu, n1, 2));
    const float c0 = exp2f(m0 - n0), c1 = exp2f(m1 - n1);
    m0 = n0; m1 = n1;
#pragma unroll
    for (int b = 0; b < 3; b++) { o[4 * b] *= c0; o[4 * b + 1] *= c0; o[4 * b + 2] *= c1; o[4 * b + 3] *= c1; }
#pragma unroll
    for (int b = 0; b < 8; b++) {
      p[2 * b] = exp_mufu(s[4 * b] - m0, s[4 * b + 1] - m0);
      p[2 * b + 1] = exp_mufu(s[4 * b + 2] - m1, s[4 * b + 3] - m1);
    }
    pin(o);
    pin(p);
    WG_FENCE();
#pragma unroll
    for (int k = 0; k < 4; k++) mma_pv(o, p[4 * k], p[4 * k + 1], p[4 * k + 2], p[4 * k + 3], dV + off + 48 * k);
    WG_COMMIT();
    wg_wait<0>();
    pin(o);
  }
}

__device__ __forceinline__ float2 store_shift(const float (&s)[32], uint8_t* qtile) {
  const int lane = threadIdx.x & 31, warp4 = (threadIdx.x >> 5) & 3, g = lane >> 2, t = lane & 3;
  float m0 = -INFINITY, m1 = -INFINITY, p0 = -INFINITY, p1 = -INFINITY;
#pragma unroll
  for (int b = 0; b < 8; b++) {
    if (!((POLY_PAT >> b) & 1)) {
      m0 = fmaxf(m0, fmaxf(s[4 * b], s[4 * b + 1]));
      m1 = fmaxf(m1, fmaxf(s[4 * b + 2], s[4 * b + 3]));
    } else {
      p0 = fmaxf(p0, fmaxf(s[4 * b], s[4 * b + 1]));
      p1 = fmaxf(p1, fmaxf(s[4 * b + 2], s[4 * b + 3]));
    }
  }
  const float k = 2361183241434822606848.0f;
  m0 = fmaxf(m0, p0 * k * k - 127.0f);
  m1 = fmaxf(m1, p1 * k * k - 127.0f);
  m0 = fmaxf(m0, __shfl_xor_sync(0xffffffffu, m0, 1)); m1 = fmaxf(m1, __shfl_xor_sync(0xffffffffu, m1, 1));
  m0 = fmaxf(m0, __shfl_xor_sync(0xffffffffu, m0, 2)); m1 = fmaxf(m1, __shfl_xor_sync(0xffffffffu, m1, 2));
  const float c0 = bf_round(m0 + 90.0f), c1 = bf_round(m1 + 90.0f);
  if (t == 0) {
    uint8_t* qp = qtile + (warp4 * 2) * 384 + 256 + g * 16 + 12;
    *reinterpret_cast<uint16_t*>(qp) = (uint16_t)(__float_as_uint(c0 * -5.421010862427522e-20f) >> 16);
    *reinterpret_cast<uint16_t*>(qp + 384) = (uint16_t)(__float_as_uint(c1 * -5.421010862427522e-20f) >> 16);
  }
  return make_float2(c0, c1);
}

__device__ __forceinline__ bool store_output(const float (&o)[12], __nv_bfloat16* __restrict__ orow) {
  const int lane = threadIdx.x & 31, warp4 = (threadIdx.x >> 5) & 3, g = lane >> 2, t = lane & 3;
  const float l0 = __shfl_sync(0xffffffffu, o[8], (lane & ~3) | 2);
  const float l1 = __shfl_sync(0xffffffffu, o[10], (lane & ~3) | 2);
  float i0, i1;
  asm("rcp.approx.ftz.f32 %0, %1;" : "=f"(i0) : "f"(l0));
  asm("rcp.approx.ftz.f32 %0, %1;" : "=f"(i1) : "f"(l1));
  uint32_t* dst0 = reinterpret_cast<uint32_t*>(orow + (warp4 * 16 + g) * D_) + t;
  uint32_t* dst1 = dst0 + 8 * (D_ / 2);
  dst0[0] = pack_bf(o[0] * i0, o[1] * i0);  dst1[0] = pack_bf(o[2] * i1, o[3] * i1);
  dst0[4] = pack_bf(o[4] * i0, o[5] * i0);  dst1[4] = pack_bf(o[6] * i1, o[7] * i1);
  if (t < 2) { dst0[8] = pack_bf(o[8] * i0, o[9] * i0); dst1[8] = pack_bf(o[10] * i1, o[11] * i1); }
  bool ok = l0 >= 7.888609052210118e-31f && l0 <= 1.0e37f && l1 >= 7.888609052210118e-31f && l1 <= 1.0e37f;
#pragma unroll
  for (int i = 0; i < 12; i++) ok = ok && fabsf(o[i]) <= 3.0e38f;
  return ok;
}

__global__ void __launch_bounds__(K2_THREADS, 1)
k2_attn(const __grid_constant__ CUtensorMap m_gate, const __grid_constant__ CUtensorMap m_up,
        const __grid_constant__ CUtensorMap m_down, const __nv_bfloat16* __restrict__ x) {
  extern __shared__ __align__(128) uint8_t smem[];
  const int tid = threadIdx.x;
  if (tid == 0) TL(1, 0);
  if (blockIdx.x < 4) {
    pdl_launch();
    moe_ffn(smem, blockIdx.x, x, &m_gate, &m_up, &m_down);
    if (tid == 0) TL(1, 5);
    return;
  }
  const int id = blockIdx.x - 4, head = id >> 2, qb = id & 3;
  const uint32_t sK = s2u(smem), sV = sK + K2_KV_BYTES, sQall = sV + K2_KV_BYTES, sZero = sQall + K2_Q_BYTES;
  const uint32_t bars = sZero + K2_ZERO_BYTES;
  if (tid == 0) {
    for (int i = 0; i < 6; i++) mbar_init(bars + 8 * i, 1);
    asm volatile("fence.mbarrier_init.release.cluster;" ::: "memory");
  }
  if (tid < K2_ZERO_BYTES / 16) reinterpret_cast<uint4*>(smem + 2 * K2_KV_BYTES + K2_Q_BYTES)[tid] = make_uint4(0, 0, 0, 0);
  fence_async_smem();
  __syncthreads();
  pdl_wait();
  pdl_launch();
  if (tid == 0) TL(1, 1);
  if (tid >= 272) g_cs[id * 240 + (tid - 272)] = 0ull;
  if (tid == 0) {
    const uint8_t* gq = reinterpret_cast<const uint8_t*>(g_qkv) + (size_t)head * HEAD_BYTES + qb * K2_Q_BYTES;
    const uint8_t* gk = reinterpret_cast<const uint8_t*>(g_qkv) + (size_t)(H_ + head) * HEAD_BYTES;
    const uint8_t* gv = gk + (size_t)H_ * HEAD_BYTES;
    mbar_expect_tx(bars + 40, K2_Q_BYTES + 6144);
    bulk_g2s(sK, gk, 6144, bars + 40);
    bulk_g2s(sQall, gq, K2_Q_BYTES, bars + 40);
    mbar_expect_tx(bars, 6144);
    bulk_g2s(sV, gv, 6144, bars);
    for (int c = 1; c < 5; c++) {
      const uint32_t off = 6144u << (c - 1), bytes = off;
      mbar_expect_tx(bars + 8 * c, 2 * bytes);
      bulk_g2s(sK + off, gk + off, bytes, bars + 8 * c);
      bulk_g2s(sV + off, gv + off, bytes, bars + 8 * c);
    }
  }
  const int wg = __reduce_max_sync(0xffffffffu, tid >> 7);
  __nv_bfloat16* orow = g_o + (qb * 512 + wg * 64) * D_ + head * 20;
  const uint64_t dK0 = mkdesc(sK, 128, 384, 0), dK1 = mkdesc(sK + 256, 0, 384, 0), dV = mkdesc(sV, 384, 128, 0);
  const uint32_t qoffA = 2 * K2_KV_BYTES + wg * 3072, qoffB = qoffA + 4 * 3072;
  const uint64_t dQA0 = mkdesc(sK + qoffA, 128, 384, 0), dQA1 = mkdesc(sK + qoffA + 256, sZero - (sK + qoffA + 256), 384, 0);
  const uint64_t dQB0 = mkdesc(sK + qoffB, 128, 384, 0), dQB1 = mkdesc(sK + qoffB + 256, sZero - (sK + qoffB + 256), 384, 0);
  float o[12];
  float s0[32], s1[32];
  uint32_t pa[8], pb[8];

#define QK(Sreg, Q0, Q1, OFF) do { mma_ss64<0>(Sreg, Q0, dK0 + (OFF)); mma_ss64<1>(Sreg, Q1, dK1 + (OFF)); } while (0)
#define PV(P, I, OFF) mma_pv(o, P[4 * (I)], P[4 * (I) + 1], P[4 * (I) + 2], P[4 * (I) + 3], dV + (OFF))
#define HALF_STEP(SA, SB, Q0, Q1, OFFP, OFFN)                               \
  WG_FENCE(); QK(SB, Q0, Q1, OFFN); WG_COMMIT();                            \
  exp_half<0>(SA, pa);                                                      \
  WG_FENCE(); PV(pa, 0, OFFP); PV(pa, 1, (OFFP) + 48); WG_COMMIT();         \
  wg_wait<2>();                                                             \
  exp_half<4>(SA, pb);                                                      \
  WG_FENCE(); PV(pb, 0, (OFFP) + 96); PV(pb, 1, (OFFP) + 144); WG_COMMIT(); \
  wg_wait<1>();                                                             \
  pin(SB);
#define LAST_STEPS(Q0, Q1)                                                  \
  {                                                                         \
    const uint64_t off = (uint64_t)(15 * 384);                              \
    HALF_STEP(s0, s1, Q0, Q1, off, off + 192)                               \
    exp_half<0>(s1, pa);                                                    \
    WG_FENCE(); PV(pa, 0, off + 192); PV(pa, 1, off + 240); WG_COMMIT();    \
    wg_wait<1>();                                                           \
    exp_half<4>(s1, pb);                                                    \
    WG_FENCE(); PV(pb, 0, off + 288); PV(pb, 1, off + 336); WG_COMMIT();    \
  }

  mbar_wait(bars + 40, 0);
  if (tid == 0) TL(1, 2);
  WG_FENCE(); QK(s0, dQA0, dQA1, 0); QK(s1, dQB0, dQB1, 0); WG_COMMIT();
  wg_wait<0>(); pin(s0); pin(s1);
  {
    const float2 c = store_shift(s0, smem + qoffA);
    store_shift(s1, smem + qoffB);
    fence_async_smem();
    const float k = 4.235164736271502e-22f;
    const float d0 = c.x * k * k, d1 = c.y * k * k;
#pragma unroll
    for (int b = 0; b < 8; b++) {
      const bool poly = (POLY_PAT >> b) & 1;
      s0[4 * b] -= poly ? d0 : c.x; s0[4 * b + 1] -= poly ? d0 : c.x;
      s0[4 * b + 2] -= poly ? d1 : c.y; s0[4 * b + 3] -= poly ? d1 : c.y;
    }
#pragma unroll
    for (int i = 0; i < 12; i++) o[i] = 0.f;
    pin(o);
    pin(s0);
    bar_sync(1 + wg, 128);
  }

  mbar_wait(bars, 0);
  if (tid == 0) TL(1, 6);
#pragma unroll 1
  for (int i = 0; i < 15; i++) {
    const uint64_t off = (uint64_t)(i * 384);
    const int in = i + 1;
    if ((in & (in - 1)) == 0) mbar_wait(bars + 8 * (32 - __clz(in)), 0);
    HALF_STEP(s0, s1, dQA0, dQA1, off, off + 192)
    HALF_STEP(s1, s0, dQA0, dQA1, off + 192, off + 384)
  }
  LAST_STEPS(dQA0, dQA1)
  WG_FENCE(); QK(s0, dQB0, dQB1, 0); WG_COMMIT();
  wg_wait<1>();
  pin(o);
  const bool okA = store_output(o, orow);
  if (tid == 0) TL(1, 3);

#pragma unroll
  for (int i = 0; i < 12; i++) o[i] = 0.f;
  pin(o);
  wg_wait<0>();
  pin(s0);
#pragma unroll 1
  for (int i = 0; i < 15; i++) {
    const uint64_t off = (uint64_t)(i * 384);
    HALF_STEP(s0, s1, dQB0, dQB1, off, off + 192)
    HALF_STEP(s1, s0, dQB0, dQB1, off + 192, off + 384)
  }
  LAST_STEPS(dQB0, dQB1)
  wg_wait<0>();
  pin(o);
  if (tid == 0) TL(1, 7);
  const bool okB = store_output(o, orow + 256 * D_);
  if (tid == 0) TL(1, 4);

  uint32_t bad;
  asm volatile("{\n.reg .pred p, q;\nsetp.eq.u32 p, %1, 0;\nbar.red.or.pred q, %2, 128, p;\nselp.u32 %0, 1, 0, q;\n}"
               : "=r"(bad) : "r"((uint32_t)(okA && okB)), "r"(1 + wg) : "memory");
  if (bad) {
#pragma unroll 1
    for (int task = 0; task < 2; task++) {
      attn_fallback(o, smem, sK, sV, task ? qoffB : qoffA, wg, task ? dQB0 : dQA0, task ? dQB1 : dQA1);
      store_output(o, orow + task * 256 * D_);
    }
  }
  if (tid == 0) TL(1, 5);
#undef QK
#undef PV
#undef HALF_STEP
#undef LAST_STEPS
}

constexpr int K3_THREADS = 288;
constexpr int K3_STAGES = 7;
constexpr int K3_B_BYTES = 80 * 640 * 2, K3_A_BYTES = 128 * 64 * 2;
constexpr int K3_SMEM = K3_STAGES * K3_A_BYTES + K3_B_BYTES + 1024 + 256;

__global__ void __launch_bounds__(K3_THREADS, 1)
k3_out(const __grid_constant__ CUtensorMap map_o, const __grid_constant__ CUtensorMap map_out,
       const __nv_bfloat16* __restrict__ x) {
  extern __shared__ uint8_t smem_raw[];
  const int tid = threadIdx.x, warp = __shfl_sync(0xffffffffu, tid >> 5, 0), lane = tid & 31;
  uint8_t* smem = smem_raw + (((s2u(smem_raw) + 1023) & ~1023u) - s2u(smem_raw));
  const uint32_t sbase = s2u(smem);
  const uint32_t sB = sbase + K3_STAGES * K3_A_BYTES;
  const uint32_t bar_full = sB + K3_B_BYTES, bar_empty = bar_full + 8 * K3_STAGES, bar_b = bar_empty + 8 * K3_STAGES;
  const int mb = blockIdx.x >> 3, nb = blockIdx.x & 7;
  if (tid == 0) TL(2, 0);
  if (warp == 8) {
    if (lane == 0) {
      asm volatile("prefetch.tensormap [%0];" ::"l"(&map_o) : "memory");
      asm volatile("prefetch.tensormap [%0];" ::"l"(&map_out) : "memory");
      for (int s = 0; s < K3_STAGES; s++) { mbar_init(bar_full + 8 * s, 1); mbar_init(bar_empty + 8 * s, 2); }
      mbar_init(bar_b, 1);
      asm volatile("fence.mbarrier_init.release.cluster;" ::: "memory");
    }
    __syncthreads();
    if (lane == 0) {
      mbar_expect_tx(bar_b, K3_B_BYTES);
      bulk_g2s(sB, reinterpret_cast<const uint8_t*>(g_wot) + (size_t)nb * K3_B_BYTES, K3_B_BYTES, bar_b);
      pdl_wait();
      TL(2, 1);
      for (int kc = 0; kc < 10; kc++) {
        const int s = kc % K3_STAGES;
        if (kc >= K3_STAGES) mbar_wait(bar_empty + 8 * s, 0);
        mbar_expect_tx(bar_full + 8 * s, K3_A_BYTES);
        tma2d(sbase + s * K3_A_BYTES, &map_o, kc * 64, mb * 128, bar_full + 8 * s);
      }

    }
    return;
  }
  const int wg = warp >> 2, g = lane >> 2, t = lane & 3;
  const int row = mb * 128 + wg * 64 + (warp & 3) * 16 + g;
  const int col = nb * 80 + 2 * t;
  uint32_t xr[20];
  float2 sp0 = make_float2(0.f, 1.f), sp1 = sp0;
#pragma unroll
  for (int j = 0; j < 20; j++) xr[j] = 0u;
  __syncthreads();
  float acc[40];
#pragma unroll
  for (int i = 0; i < 40; i++) acc[i] = 0.f;
  int i0 = -1, i1 = -1;
#pragma unroll 1
  for (int trip = 0; trip < 2; trip++) {
    const bool real = trip != 0;
    if (real) {
      sp0 = __ldcg(&g_statp[row]); sp1 = __ldcg(&g_statp[row + 8]);
#pragma unroll
      for (int j = 0; j < 10; j++) {
        xr[2 * j] = __ldg(reinterpret_cast<const uint32_t*>(x + row * D_ + col + 8 * j));
        xr[2 * j + 1] = __ldg(reinterpret_cast<const uint32_t*>(x + (row + 8) * D_ + col + 8 * j));
      }
      pdl_wait();
      if (tid < 16) { g_rp[blockIdx.x * 16 + tid] = 0ull; g_stat[blockIdx.x * 16 + tid] = 0ull; }
      i0 = __ldcg(&g_idx[0]); i1 = __ldcg(&g_idx[1]);
      mbar_wait(bar_b, 0);
#pragma unroll 1
      for (int kc = 0; kc < 10; kc++) {
        const int s = kc % K3_STAGES;
        mbar_wait(bar_full + 8 * s, (kc / K3_STAGES) & 1);
        if (tid == 0 && kc == 0) TL(2, 3);
        const uint64_t da = mkdesc(sbase + s * K3_A_BYTES + wg * 8192, 16, 1024, 1);
        const uint64_t db = mkdesc(sB + kc * 10240, 128, 1024, 0);
        WG_FENCE();
#pragma unroll
        for (int kk = 0; kk < 4; kk++) mma_ss80(acc, da + kk * 2, db + kk * 16, (kc | kk) != 0);
        WG_COMMIT();
        if (kc > 0) {
          wg_wait<1>();
          if ((tid & 127) == 0 && kc - 1 < 10 - K3_STAGES) mbar_arrive(bar_empty + 8 * (kc - 1));
        }
      }
      wg_wait<0>();
      pin(acc);
      if (tid == 0) TL(2, 4);
      bar_sync(1, 256);
    }
    const uint32_t stg = sB + ((wg * 64 + (warp & 3) * 16 + g) * 40 + t) * 4;
#pragma unroll
    for (int h = 0; h < 2; h++) {
      const float2 sp = h ? sp1 : sp0;
      const uint32_t m2 = pack_bf(sp.x, sp.x);
      uint32_t n[10];
#pragma unroll
      for (int j = 0; j < 10; j++) {
        const uint32_t d = bf2_sub(xr[2 * j + h], m2);
        n[j] = pack_bf(bf_lo(d) * sp.y, bf_hi(d) * sp.y);
      }
      const int r = row + 8 * h;
      if (r == i0 || r == i1) {
        const uint32_t* up = g_upd + (r == i0 ? 0 : D_ / 2) + (col >> 1);
#pragma unroll
        for (int j = 0; j < 10; j++) n[j] = bf2_add(n[j], __ldcg(up + 4 * j));
      }
#pragma unroll
      for (int j = 0; j < 10; j++) {
        const uint32_t a = bf2_add(xr[2 * j + h], pack_bf(acc[4 * j + 2 * h], acc[4 * j + 2 * h + 1]));
        sts_if(real, stg + (h * 320 + 4 * j) * 4, bf2_add(a, n[j]));
      }
    }
  }
  fence_async_smem();
  bar_sync(2 + wg, 128);
  if ((tid & 127) == 0) {
    asm volatile("cp.async.bulk.tensor.2d.global.shared::cta.bulk_group [%0, {%2, %3}], [%1];"
                 ::"l"(&map_out), "r"(sB + wg * 64 * 160), "r"(nb * 80), "r"(mb * 128 + wg * 64) : "memory");
    asm volatile("cp.async.bulk.commit_group;" ::: "memory");
    asm volatile("cp.async.bulk.wait_group.read 0;" ::: "memory");
  }
  if (tid == 0) TL(2, 5);
}

typedef CUresult (*EncodeFn)(CUtensorMap*, CUtensorMapDataType, cuuint32_t, void*, const cuuint64_t*, const cuuint64_t*,
                             const cuuint32_t*, const cuuint32_t*, CUtensorMapInterleave, CUtensorMapSwizzle,
                             CUtensorMapL2promotion, CUtensorMapFloatOOBfill);

CUtensorMap make_map(EncodeFn fn, const void* ptr, uint64_t cols, uint64_t rows, uint32_t box_cols, uint32_t box_rows,
                     CUtensorMapSwizzle swz) {
  CUtensorMap m;
  const cuuint64_t dims[2] = {cols, rows};
  const cuuint64_t strides[1] = {cols * 2};
  const cuuint32_t box[2] = {box_cols, box_rows};
  const cuuint32_t es[2] = {1, 1};
  fn(&m, CU_TENSOR_MAP_DATA_TYPE_BFLOAT16, 2, const_cast<void*>(ptr), dims, strides, box, es, CU_TENSOR_MAP_INTERLEAVE_NONE,
     swz, CU_TENSOR_MAP_L2_PROMOTION_L2_128B, CU_TENSOR_MAP_FLOAT_OOB_FILL_NONE);
  return m;
}

}

extern "C" void kernel_launch(void* const* d_in, const int* in_sizes, int n_in, void* d_out, int out_size) {
  (void)in_sizes; (void)n_in; (void)out_size;
  const __nv_bfloat16* x = (const __nv_bfloat16*)d_in[0];
  const __nv_bfloat16* wqkv = (const __nv_bfloat16*)d_in[1];
  const __nv_bfloat16* wo = (const __nv_bfloat16*)d_in[2];
  const __nv_bfloat16* w_r = (const __nv_bfloat16*)d_in[4];
  const __nv_bfloat16* w_gate = (const __nv_bfloat16*)d_in[5];
  const __nv_bfloat16* w_up = (const __nv_bfloat16*)d_in[6];
  const __nv_bfloat16* w_down = (const __nv_bfloat16*)d_in[7];

  static EncodeFn encode = nullptr;
  static void* p_o = nullptr;
  if (!encode) {
    void* fn = nullptr;
    cudaDriverEntryPointQueryResult qr;
    cudaGetDriverEntryPoint("cuTensorMapEncodeTiled", &fn, cudaEnableDefault, &qr);
    encode = (EncodeFn)fn;
    cudaGetSymbolAddress(&p_o, g_o);
    cudaFuncSetAttribute(k1_ln_qkv, cudaFuncAttributeMaxDynamicSharedMemorySize, K1_SMEM);
    cudaFuncSetAttribute(k2_attn, cudaFuncAttributeMaxDynamicSharedMemorySize, K2_SMEM);
    cudaFuncSetAttribute(k3_out, cudaFuncAttributeMaxDynamicSharedMemorySize, K3_SMEM);
  }
  const CUtensorMap map_x = make_map(encode, x, D_, S_, 64, 128, CU_TENSOR_MAP_SWIZZLE_128B);
  const CUtensorMap map_w = make_map(encode, wqkv, 3 * D_, D_, 64, 64, CU_TENSOR_MAP_SWIZZLE_128B);
  const CUtensorMap map_o = make_map(encode, p_o, D_, S_, 64, 128, CU_TENSOR_MAP_SWIZZLE_128B);
  const CUtensorMap map_gate = make_map(encode, w_gate, F_, D_, 64, 128, CU_TENSOR_MAP_SWIZZLE_128B);
  const CUtensorMap map_up = make_map(encode, w_up, F_, D_, 64, 128, CU_TENSOR_MAP_SWIZZLE_128B);
  const CUtensorMap map_down = make_map(encode, w_down, D_, F_, 64, 128, CU_TENSOR_MAP_SWIZZLE_128B);
  const CUtensorMap map_out = make_map(encode, d_out, D_, S_, 80, 64, CU_TENSOR_MAP_SWIZZLE_NONE);

  cudaStream_t st = cudaStreamPerThread;
  k1_ln_qkv<<<128, K1_THREADS, K1_SMEM, st>>>(map_x, map_w, x, wqkv, w_r, wo, w_gate, w_up, w_down);

  cudaLaunchAttribute at[1];
  at[0].id = cudaLaunchAttributeProgrammaticStreamSerialization;
  at[0].val.programmaticStreamSerializationAllowed = 1;
  cudaLaunchConfig_t cfg = {};
  cfg.stream = st;
  cfg.attrs = at;
  cfg.numAttrs = 1;
  cfg.gridDim = dim3(132); cfg.blockDim = dim3(K2_THREADS); cfg.dynamicSmemBytes = K2_SMEM;
  cudaLaunchKernelEx(&cfg, k2_attn, map_gate, map_up, map_down, x);
  cfg.gridDim = dim3(128); cfg.blockDim = dim3(K3_THREADS); cfg.dynamicSmemBytes = K3_SMEM;
  cudaLaunchKernelEx(&cfg, k3_out, map_o, map_out, x);
}
```

```cpp
#include <cuda_runtime.h>
#include <cuda_bf16.h>
#include <cuda.h>
#include <stdint.h>

namespace {

constexpr int S_ = 2048, D_ = 640, H_ = 32, F_ = 1728;

constexpr int HEAD_ELEMS = 256 * 192;
constexpr int HEAD_BYTES = HEAD_ELEMS * 2;
__device__ __align__(1024) __nv_bfloat16 g_o[S_ * D_];
__device__ __align__(1024) __nv_bfloat16 g_qkv[3 * H_ * HEAD_ELEMS];
__device__ __align__(1024) __nv_bfloat16 g_wot[D_ * D_];
__device__ unsigned long long g_rp[S_];
__device__ unsigned long long g_stat[S_];
__device__ unsigned long long g_cs[3 * D_];
__device__ float g_ypart[4 * 2 * D_];
__device__ uint32_t g_upd[D_];
__device__ int g_idx[2];
__device__ float2 g_statp[S_];
__device__ unsigned g_ffn_done;

constexpr unsigned POLY_PAT = 0xDAu;

#define TL(k, i) do {} while (0)

__device__ __forceinline__ uint32_t s2u(const void* p) { return (uint32_t)__cvta_generic_to_shared(p); }
__device__ __forceinline__ void mbar_init(uint32_t bar, uint32_t cnt) {
  asm volatile("mbarrier.init.shared::cta.b64 [%0], %1;" ::"r"(bar), "r"(cnt) : "memory");
}
__device__ __forceinline__ void mbar_expect_tx(uint32_t bar, uint32_t bytes) {
  asm volatile("mbarrier.arrive.expect_tx.shared::cta.b64 _, [%0], %1;" ::"r"(bar), "r"(bytes) : "memory");
}
__device__ __forceinline__ void mbar_arrive(uint32_t bar) {
  asm volatile("mbarrier.arrive.shared::cta.b64 _, [%0];" ::"r"(bar) : "memory");
}
__device__ __forceinline__ bool mbar_try(uint32_t bar, uint32_t parity) {
  uint32_t ok;
  asm volatile("{\n.reg .pred p;\nmbarrier.try_wait.parity.shared::cta.b64 p, [%1], %2;\nselp.u32 %0, 1, 0, p;\n}"
               : "=r"(ok) : "r"(bar), "r"(parity) : "memory");
  return ok != 0;
}
__device__ __forceinline__ void mbar_wait(uint32_t bar, uint32_t parity) {
  if (mbar_try(bar, parity)) return;
  for (int it = 0; !mbar_try(bar, parity); ++it)
    if (it > (1 << 22)) __trap();
}
__device__ __forceinline__ void bulk_g2s(uint32_t dst, const void* src, uint32_t bytes, uint32_t bar) {
  asm volatile("cp.async.bulk.shared::cluster.global.mbarrier::complete_tx::bytes [%0], [%1], %2, [%3];"
               ::"r"(dst), "l"(src), "r"(bytes), "r"(bar) : "memory");
}
__device__ __forceinline__ void tma2d(uint32_t dst, const CUtensorMap* map, int c0, int c1, uint32_t bar) {
  asm volatile("cp.async.bulk.tensor.2d.shared::cluster.global.mbarrier::complete_tx::bytes [%0], [%1, {%3, %4}], [%2];"
               ::"r"(dst), "l"(map), "r"(bar), "r"(c0), "r"(c1) : "memory");
}
__device__ __forceinline__ void tma3d(uint32_t dst, const CUtensorMap* map, int c0, int c1, int c2, uint32_t bar) {
  asm volatile("cp.async.bulk.tensor.3d.shared::cluster.global.mbarrier::complete_tx::bytes [%0], [%1, {%3, %4, %5}], [%2];"
               ::"r"(dst), "l"(map), "r"(bar), "r"(c0), "r"(c1), "r"(c2) : "memory");
}
__device__ __forceinline__ void pdl_launch() { asm volatile("griddepcontrol.launch_dependents;" ::: "memory"); }
__device__ __forceinline__ void pdl_wait() { asm volatile("griddepcontrol.wait;" ::: "memory"); }
__device__ __forceinline__ void fence_async_smem() { asm volatile("fence.proxy.async.shared::cta;" ::: "memory"); }
__device__ __forceinline__ void bar_sync(int id, int n) { asm volatile("bar.sync %0, %1;" ::"r"(id), "r"(n) : "memory"); }
constexpr uint32_t tag = 1;
__device__ __forceinline__ void put_packet(unsigned long long* p, uint32_t payload, uint32_t tag_) {
  asm volatile("st.relaxed.gpu.global.b64 [%0], %1;" ::"l"(p), "l"(((unsigned long long)tag_ << 32) | payload) : "memory");
}
__device__ __forceinline__ unsigned long long ld_packet(const unsigned long long* p) {
  unsigned long long v;
  asm volatile("ld.relaxed.gpu.global.b64 %0, [%1];" : "=l"(v) : "l"(p) : "memory");
  return v;
}
__device__ __forceinline__ uint32_t get_packet(const unsigned long long* p, uint32_t tag_) {
  unsigned long long v = ld_packet(p);
  for (int it = 0; (uint32_t)(v >> 32) != tag_; ++it) {
    if (it > (1 << 22)) __trap();
    v = ld_packet(p);
  }
  return (uint32_t)v;
}

#define WG_FENCE() asm volatile("wgmma.fence.sync.aligned;" ::: "memory")
#define WG_COMMIT() asm volatile("wgmma.commit_group.sync.aligned;" ::: "memory")
template <int N> __device__ __forceinline__ void wg_wait() {
  asm volatile("wgmma.wait_group.sync.aligned %0;" ::"n"(N) : "memory");
}
template <int N> __device__ __forceinline__ void pin(float (&d)[N]) {
#pragma unroll
  for (int i = 0; i < N; i++) asm volatile("" : "+f"(d[i])::"memory");
}
template <int N> __device__ __forceinline__ void pin(uint32_t (&d)[N]) {
#pragma unroll
  for (int i = 0; i < N; i++) asm volatile("" : "+r"(d[i])::"memory");
}
__device__ __forceinline__ uint64_t mkdesc(uint32_t addr, uint32_t lbo, uint32_t sbo, uint32_t swz) {
  return (uint64_t)((addr & 0x3FFFF) >> 4) | ((uint64_t)(lbo >> 4) << 16) | ((uint64_t)(sbo >> 4) << 32) |
         ((uint64_t)swz << 62);
}

#define R4(d, i) "+f"(d[i]), "+f"(d[i + 1]), "+f"(d[i + 2]), "+f"(d[i + 3])
#define R8(d, i) R4(d, i), R4(d, i + 4)
#define R16(d, i) R8(d, i), R8(d, i + 8)
#define R32(d, i) R16(d, i), R16(d, i + 16)

template <int ACC> __device__ __forceinline__ void mma_ss64(float (&d)[32], uint64_t da, uint64_t db) {
  asm volatile(
      "wgmma.mma_async.sync.aligned.m64n64k16.f32.bf16.bf16 "
      "{%0,%1,%2,%3,%4,%5,%6,%7,%8,%9,%10,%11,%12,%13,%14,%15,%16,%17,%18,%19,%20,%21,%22,%23,%24,%25,%26,%27,%28,%29,%30,%31},"
      "%32, %33, %34, 1, 1, 0, 0;"
      : R32(d, 0) : "l"(da), "l"(db), "n"(ACC));
}
__device__ __forceinline__ void mma_pv(float (&d)[12], uint32_t a0, uint32_t a1, uint32_t a2, uint32_t a3, uint64_t db) {
  asm volatile(
      "wgmma.mma_async.sync.aligned.m64n24k16.f32.bf16.bf16 "
      "{%0,%1,%2,%3,%4,%5,%6,%7,%8,%9,%10,%11}, {%12,%13,%14,%15}, %16, 1, 1, 1, 1;"
      : R8(d, 0), R4(d, 8) : "r"(a0), "r"(a1), "r"(a2), "r"(a3), "l"(db));
}
__device__ __forceinline__ void mma_ss240(float (&d)[120], uint64_t da, uint64_t db, int acc) {
  asm volatile(
      "{\n.reg .pred p;\nsetp.ne.b32 p, %122, 0;\n"
      "wgmma.mma_async.sync.aligned.m64n240k16.f32.bf16.bf16 "
      "{%0,%1,%2,%3,%4,%5,%6,%7,%8,%9,%10,%11,%12,%13,%14,%15,%16,%17,%18,%19,%20,%21,%22,%23,%24,%25,%26,%27,%28,%29,"
      "%30,%31,%32,%33,%34,%35,%36,%37,%38,%39,%40,%41,%42,%43,%44,%45,%46,%47,%48,%49,%50,%51,%52,%53,%54,%55,%56,%57,%58,%59,"
      "%60,%61,%62,%63,%64,%65,%66,%67,%68,%69,%70,%71,%72,%73,%74,%75,%76,%77,%78,%79,%80,%81,%82,%83,%84,%85,%86,%87,%88,%89,"
      "%90,%91,%92,%93,%94,%95,%96,%97,%98,%99,%100,%101,%102,%103,%104,%105,%106,%107,%108,%109,%110,%111,%112,%113,%114,%115,%116,%117,%118,%119},"
      "%120, %121, p, 1, 1, 0, 1;\n}"
      : R32(d, 0), R32(d, 32), R32(d, 64), R16(d, 96), R8(d, 112)
      : "l"(da), "l"(db), "r"(acc));
}
__device__ __forceinline__ void mma_ss80(float (&d)[40], uint64_t da, uint64_t db, int acc) {
  asm volatile(
      "{\n.reg .pred p;\nsetp.ne.b32 p, %42, 0;\n"
      "wgmma.mma_async.sync.aligned.m64n80k16.f32.bf16.bf16 "
      "{%0,%1,%2,%3,%4,%5,%6,%7,%8,%9,%10,%11,%12,%13,%14,%15,%16,%17,%18,%19,%20,%21,%22,%23,%24,%25,%26,%27,%28,%29,"
      "%30,%31,%32,%33,%34,%35,%36,%37,%38,%39},"
      "%40, %41, p, 1, 1, 0, 1;\n}"
      : R32(d, 0), R8(d, 32)
      : "l"(da), "l"(db), "r"(acc));
}

__device__ __forceinline__ void sts_if(bool p, uint32_t addr, uint32_t v) {
  asm volatile("{\n.reg .pred p;\nsetp.ne.u32 p, %2, 0;\n@p st.shared.b32 [%0], %1;\n}" ::"r"(addr), "r"(v), "r"((uint32_t)p));
}
__device__ __forceinline__ float bf_round(float v) {
  uint32_t r;
  asm("cvt.rn.bf16x2.f32 %0, %1, %2;" : "=r"(r) : "f"(v), "f"(0.0f));
  return __uint_as_float(r);
}
__device__ __forceinline__ uint32_t pack_bf(float lo, float hi) {
  uint32_t r;
  asm("cvt.rn.bf16x2.f32 %0, %1, %2;" : "=r"(r) : "f"(hi), "f"(lo));
  return r;
}
__device__ __forceinline__ uint32_t bf2_add(uint32_t a, uint32_t b) {
  uint32_t r;
  asm("add.rn.bf16x2 %0, %1, %2;" : "=r"(r) : "r"(a), "r"(b));
  return r;
}
__device__ __forceinline__ uint32_t bf2_sub(uint32_t a, uint32_t b) {
  uint32_t r;
  asm("sub.rn.bf16x2 %0, %1, %2;" : "=r"(r) : "r"(a), "r"(b));
  return r;
}
__device__ __forceinline__ float bf_lo(uint32_t u) { return __uint_as_float(u << 16); }
__device__ __forceinline__ float bf_hi(uint32_t u) { return __uint_as_float(u & 0xFFFF0000u); }

constexpr int K1_THREADS = 384;
constexpr int K1_STAGES = 4;
constexpr int K1_A_BYTES = 128 * 64 * 2, K1_B_BYTES = 4 * 64 * 64 * 2, K1_STAGE = K1_A_BYTES + K1_B_BYTES;
constexpr int K1_AUX = K1_STAGES * K1_STAGE;
constexpr int K1_SMEM = K1_AUX + 128 + 1024 + 1024 + 3072 + 1024;

__device__ __forceinline__ void ln_stats2(const uint2 (&xa)[5], const uint2 (&xb)[5], const uint2 (&wv)[5], int row, int lane) {
  float s[2] = {0.f, 0.f}, q[2] = {0.f, 0.f}, tw[2] = {0.f, 0.f}, x0[2], sw = 0.f;
  x0[0] = bf_lo(__shfl_sync(~0u, xa[0].x, 0));
  x0[1] = bf_lo(__shfl_sync(~0u, xb[0].x, 0));
#pragma unroll
  for (int i = 0; i < 5; i++) {
    const uint2 w = wv[i];
    const float w0 = bf_lo(w.x), w1 = bf_hi(w.x), w2 = bf_lo(w.y), w3 = bf_hi(w.y);
    sw += (w0 + w1) + (w2 + w3);
#pragma unroll
    for (int r = 0; r < 2; r++) {
      const uint2 u = r ? xb[i] : xa[i];
      const float d0 = bf_lo(u.x) - x0[r], d1 = bf_hi(u.x) - x0[r], d2 = bf_lo(u.y) - x0[r], d3 = bf_hi(u.y) - x0[r];
      s[r] += (d0 + d1) + (d2 + d3);
      q[r] = fmaf(d0, d0, fmaf(d1, d1, fmaf(d2, d2, fmaf(d3, d3, q[r]))));
      tw[r] = fmaf(d0, w0, fmaf(d1, w1, fmaf(d2, w2, fmaf(d3, w3, tw[r]))));
    }
  }
#pragma unroll
  for (int o = 16; o; o >>= 1) {
    s[0] += __shfl_xor_sync(~0u, s[0], o); q[0] += __shfl_xor_sync(~0u, q[0], o); tw[0] += __shfl_xor_sync(~0u, tw[0], o);
    s[1] += __shfl_xor_sync(~0u, s[1], o); q[1] += __shfl_xor_sync(~0u, q[1], o); tw[1] += __shfl_xor_sync(~0u, tw[1], o);
    sw += __shfl_xor_sync(~0u, sw, o);
  }
  const bool second = lane & 1;
  const float xs = second ? x0[1] : x0[0];
  const float md = (second ? s[1] : s[0]) * (1.0f / D_);
  const float var = fmaxf(fmaf(-md, md, (second ? q[1] : q[0]) * (1.0f / D_)), 0.f);
  const float m = bf_round(md + xs);
  const float den = bf_round(__fsqrt_rn(bf_round(bf_round(var) + 1e-5f)));
  if (lane < 2) {
    const uint32_t pay = __float_as_uint(m) | (__float_as_uint(den) >> 16);
    put_packet(&g_stat[row + lane], pay, tag);
    g_statp[row + lane] = make_float2(m, __fdiv_rn(1.0f, den));
    const float r = __fdiv_rn(fmaf(xs - m, sw, second ? tw[1] : tw[0]), den);
    put_packet(&g_rp[row + lane], __float_as_uint(bf_round(r)), tag);
  }
}

__device__ __forceinline__ void k1_store_duty(uint32_t sbase, int warp, int lane, int mb, int nb) {
#pragma unroll 1
  for (int ev = 0; ev < 6; ev++) {
    bar_sync(3 + ev, 256);
    if (lane == 0) {
      const int hl = 4 * (ev >> 1) + (warp - 8), wg = ev & 1;
      uint8_t* dst = reinterpret_cast<uint8_t*>(g_qkv) + (size_t)(nb * 12 + hl) * HEAD_BYTES + mb * 6144 + wg * 3072;
      asm volatile("cp.async.bulk.global.shared::cta.bulk_group [%0], [%1], 3072;"
                   ::"l"(dst), "r"(sbase + hl * 6144 + wg * 3072) : "memory");
      asm volatile("cp.async.bulk.commit_group;" ::: "memory");
    }
  }
  if (lane == 0) asm volatile("cp.async.bulk.wait_group.read 0;" ::: "memory");
}

__global__ void __launch_bounds__(K1_THREADS, 1)
k1_ln_qkv(const __grid_constant__ CUtensorMap map_x, const __grid_constant__ CUtensorMap map_w,
          const __grid_constant__ CUtensorMap map_w4, const __grid_constant__ CUtensorMap map_w3,
          const __nv_bfloat16* __restrict__ x, const __nv_bfloat16* __restrict__ wqkv,
          const __nv_bfloat16* __restrict__ w_r, const __nv_bfloat16* __restrict__ wo) {
  extern __shared__ uint8_t smem_raw[];
  const int tid = threadIdx.x, warp = __shfl_sync(0xffffffffu, tid >> 5, 0), lane = tid & 31;
  const int bid = blockIdx.x;
  if (tid == 0) TL(0, 0);
  uint8_t* smem = smem_raw + (((s2u(smem_raw) + 1023) & ~1023u) - s2u(smem_raw));
  const uint32_t sbase = s2u(smem);
  const uint32_t bar_full = sbase + K1_AUX, bar_empty = bar_full + 8 * K1_STAGES;
  float2* s_stat = reinterpret_cast<float2*>(smem + K1_AUX + 128);
  float* s_cs = reinterpret_cast<float*>(smem + K1_AUX + 128 + 1024);
  const int mb = bid & 15, nb = bid >> 4;

  if (tid == 256) {
    asm volatile("prefetch.tensormap [%0];" ::"l"(&map_x) : "memory");
    asm volatile("prefetch.tensormap [%0];" ::"l"(nb < 7 ? &map_w4 : &map_w3) : "memory");
    for (int s = 0; s < K1_STAGES; s++) { mbar_init(bar_full + 8 * s, 1); mbar_init(bar_empty + 8 * s, 2); }
    asm volatile("fence.mbarrier_init.release.cluster;" ::: "memory");
  }
  __syncthreads();
  pdl_launch();

  if (warp == 8) {
    if (lane == 0) {
      for (int kc = 0; kc < 10; kc++) {
        const int s = kc % K1_STAGES;
        if (kc >= K1_STAGES) mbar_wait(bar_empty + 8 * s, ((kc / K1_STAGES) - 1) & 1);
        mbar_expect_tx(bar_full + 8 * s, K1_STAGE);
        const uint32_t sa = sbase + s * K1_STAGE, sb = sa + K1_A_BYTES;
        tma3d(sb, nb < 7 ? &map_w4 : &map_w3, nb * 240, kc * 64, 0, bar_full + 8 * s);
        if (nb == 7) tma2d(sb + 3 * 8192, &map_w, nb * 240 + 192, kc * 64, bar_full + 8 * s);
        tma2d(sa, &map_x, kc * 64, mb * 128, bar_full + 8 * s);
      }
    }
    __syncwarp();
    k1_store_duty(sbase, warp, lane, mb, nb);
    return;
  }

  if (warp > 8) {
    const int at = tid - 288;
    float* s_part = reinterpret_cast<float*>(smem + K1_AUX + 128 + 2048);
    mbar_wait(bar_full, 0);
    if (mb < 15) {
      const int half = at & 1, rg = at >> 1;
      const uint4* wp = reinterpret_cast<const uint4*>(wqkv + (size_t)rg * (3 * D_) + nb * 240 + mb * 16) + half;
      uint4 v[14];
#pragma unroll
      for (int k = 0; k < 14; k++)
        v[k] = (rg + 48 * k < D_) ? __ldg(wp + (size_t)k * 48 * (3 * D_ / 8)) : make_uint4(0, 0, 0, 0);
      float c[8];
#pragma unroll
      for (int i = 0; i < 8; i++) c[i] = 0.f;
#pragma unroll
      for (int k = 0; k < 14; k++) {
        c[0] += bf_lo(v[k].x); c[1] += bf_hi(v[k].x); c[2] += bf_lo(v[k].y); c[3] += bf_hi(v[k].y);
        c[4] += bf_lo(v[k].z); c[5] += bf_hi(v[k].z); c[6] += bf_lo(v[k].w); c[7] += bf_hi(v[k].w);
      }
#pragma unroll
      for (int o = 2; o < 32; o <<= 1)
#pragma unroll
        for (int i = 0; i < 8; i++) c[i] += __shfl_xor_sync(0xffffffffu, c[i], o);
      if (lane < 2) {
#pragma unroll
        for (int i = 0; i < 8; i++) s_part[(warp - 9) * 16 + lane * 8 + i] = c[i];
      }
      bar_sync(1, 96);
      if (at < 16)
        put_packet(&g_cs[nb * 240 + mb * 16 + at], __float_as_uint(s_part[at] + s_part[16 + at] + s_part[32 + at]), tag);
    }
    if (at == 0) TL(0, 1);
    uint4 wov[5];
#pragma unroll
    for (int i = 0; i < 5; i++) {
      const int j = at + 96 * i;
      if (j < 400) wov[i] = __ldg(reinterpret_cast<const uint4*>(wo) + bid * 400 + j);
    }
    {
      const unsigned long long* ps = &g_stat[mb * 128 + at];
      const unsigned long long* pc = &g_cs[nb * 240 + at];
      unsigned long long v0, v1, c0, c1, c2;
      for (int it = 0;; ++it) {
        v0 = ld_packet(ps);
        v1 = at < 32 ? ld_packet(ps + 96) : (1ull << 32);
        c0 = ld_packet(pc);
        c1 = ld_packet(pc + 96);
        c2 = at < 48 ? ld_packet(pc + 192) : (1ull << 32);
        if (((uint32_t)(v0 >> 32) & (uint32_t)(v1 >> 32) & (uint32_t)(c0 >> 32) & (uint32_t)(c1 >> 32) & (uint32_t)(c2 >> 32)) == tag) break;
        if (it > (1 << 22)) __trap();
      }
      s_stat[at] = make_float2(__uint_as_float((uint32_t)v0 & 0xFFFF0000u), __fdiv_rn(1.0f, __uint_as_float((uint32_t)v0 << 16)));
      if (at < 32)
        s_stat[96 + at] = make_float2(__uint_as_float((uint32_t)v1 & 0xFFFF0000u), __fdiv_rn(1.0f, __uint_as_float((uint32_t)v1 << 16)));
      s_cs[at] = __uint_as_float((uint32_t)c0);
      s_cs[96 + at] = __uint_as_float((uint32_t)c1);
      if (at < 48) s_cs[192 + at] = __uint_as_float((uint32_t)c2);
    }
    __threadfence_block();
    asm volatile("bar.arrive 2, 352;" ::: "memory");
    if (at == 0) TL(0, 2);
#pragma unroll
    for (int i = 0; i < 5; i++) {
      const int j = at + 96 * i;
      if (j < 400) {
        const int li = bid * 400 + j, k = li / 80, cv = li % 80;
        const int dst = ((((cv / 10) * 10 + (k >> 6)) * 10 + (cv % 10)) * 8 + ((k >> 3) & 7)) * 8 + (k & 7);
        reinterpret_cast<uint4*>(g_wot)[dst] = wov[i];
      }
    }
    k1_store_duty(sbase, warp, lane, mb, nb);
    return;
  }

  const int wg = warp >> 2;
  const int lrow = mb * 128 + nb * 16 + warp * 2;
  uint2 xa[5], xb[5], wv[5];
#pragma unroll
  for (int i = 0; i < 5; i++) {
    xa[i] = __ldg(reinterpret_cast<const uint2*>(x + lrow * D_) + i * 32 + lane);
    xb[i] = __ldg(reinterpret_cast<const uint2*>(x + (lrow + 1) * D_) + i * 32 + lane);
    wv[i] = __ldg(reinterpret_cast<const uint2*>(w_r) + i * 32 + lane);
  }
  float acc[120];
  {
    constexpr bool real = true;
    {
      ln_stats2(xa, xb, wv, lrow, lane);
      if (tid == 0) TL(0, 6);
#pragma unroll 1
      for (int kc = 0; kc < 10; kc++) {
        const int s = kc % K1_STAGES;

        mbar_wait(bar_full + 8 * s, (kc / K1_STAGES) & 1);

        if (tid == 0 && kc == 0) TL(0, 3);
        const uint32_t sa = sbase + s * K1_STAGE + wg * 8192, sb = sbase + s * K1_STAGE + K1_A_BYTES;
        const uint64_t da = mkdesc(sa, 16, 1024, 1), db = mkdesc(sb, 8192, 1024, 1);
        WG_FENCE();
#pragma unroll
        for (int kk = 0; kk < 4; kk++) mma_ss240(acc, da + kk * 2, db + kk * 128, (kc | kk) != 0);
        WG_COMMIT();
        if (kc > 0) {
          wg_wait<1>();
          if ((tid & 127) == 0 && kc - 1 + K1_STAGES < 10) mbar_arrive(bar_empty + 8 * ((kc - 1) % K1_STAGES));
        }
      }
      wg_wait<0>();
      pin(acc);
      if (tid == 0) TL(0, 4);
      bar_sync(2, 352);
    }

    const int g = lane >> 2, t = lane & 3;
    const int rl = wg * 64 + (warp & 3) * 16 + g;
    const int grp = rl >> 3;
    const bool poly0 = (POLY_PAT >> (grp & 7)) & 1, poly1 = (POLY_PAT >> ((grp + 1) & 7)) & 1;
    const float qs = 0.22360679774997896f * 1.4426950408889634f * 5.421010862427522e-20f;
    const float kbig = 18446744073709551616.0f, ksmall = 3.308722450212111e-24f;
    const float2 st0 = s_stat[rl], st1 = s_stat[rl + 8];
    const float nm0 = -st0.x, nm1 = -st1.x;
    constexpr int HS = 1536;
    const uint32_t gb = sbase + (grp * 96 + g * 4) * 4;
    const float* const csp = s_cs + 2 * t;
#pragma unroll
    for (int bt = 0; bt < 3; bt++) {
      const int type = (nb * 12 + 4 * bt) >> 5;
      const bool isv = type == 2;
      const float s0 = st0.y * (type == 0 ? qs : (isv ? 1.0f : (poly0 ? ksmall : kbig)));
      const float s1 = st1.y * (type == 0 ? qs : (isv ? 1.0f : (poly1 ? ksmall : kbig)));
      const uint32_t hb = gb + 4 * bt * HS * 4;
      uint32_t p[5];
      p[0] = hb + 4 * t;
      p[1] = hb + 4 * ((t == 3 && !isv) ? 64 : 32 + t);
      p[2] = hb + 4 * (t < 2 ? 64 + t + (isv ? 0 : 1) : HS + t - 2);
      p[3] = hb + 4 * (t < 2 ? 2 + t : 30 + t);
      p[4] = hb + 4 * (t == 0 ? 34 : (isv ? (t == 1 ? 35 : 62 + t) : 63 + t));
      float2 csv[10];
#pragma unroll
      for (int jj = 0; jj < 10; jj++) csv[jj] = *reinterpret_cast<const float2*>(csp + 8 * (10 * bt + jj));
#pragma unroll
      for (int jj = 0; jj < 10; jj++) {
        const int j = 10 * bt + jj;
        const int h0 = (8 * jj) / 20;
        const float2 cs = csv[jj];
        const uint32_t q = p[jj % 5] + h0 * HS * 4;
        sts_if(real, q, pack_bf(fmaf(nm0, cs.x, acc[4 * j]) * s0, fmaf(nm0, cs.y, acc[4 * j + 1]) * s0));
        sts_if(real, q + 384, pack_bf(fmaf(nm1, cs.x, acc[4 * j + 2]) * s1, fmaf(nm1, cs.y, acc[4 * j + 3]) * s1));
      }
      const uint32_t cb = hb + t * HS * 4;
      const uint32_t a0 = type == 0 ? 0x00001F80u : (isv ? 0x00003F80u : (poly0 ? 0x00001E00u : 0u));
      const uint32_t a1 = type == 0 ? 0x00001F80u : (isv ? 0x00003F80u : (poly1 ? 0x00001E00u : 0u));
      const uint32_t b0 = type == 0 ? 0x1F800000u : (isv ? 0u : (poly0 ? 0x987E1880u : 0x64F05F80u));
      const uint32_t b1 = type == 0 ? 0x1F800000u : (isv ? 0u : (poly1 ? 0x987E1880u : 0x64F05F80u));
      sts_if(real, cb + (isv ? 66 : 35) * 4, a0); sts_if(real, cb + 384 + (isv ? 66 : 35) * 4, a1);
      sts_if(real, cb + 67 * 4, b0); sts_if(real, cb + 384 + 67 * 4, b1);
      if (real) {
        fence_async_smem();
        asm volatile("bar.arrive %0, 256;" ::"r"(3 + 2 * bt + wg) : "memory");
      }
    }
  }
  if (tid == 0) TL(0, 5);
}

constexpr int K2_THREADS = 512;
constexpr int K2_KV_BYTES = 98304, K2_Q_BYTES = 24576, K2_ZERO_BYTES = 2816;
constexpr int K2_SMEM = 2 * K2_KV_BYTES + K2_Q_BYTES + K2_ZERO_BYTES + 256;

__device__ __forceinline__ float ex2(float v) {
  float r;
  asm("ex2.approx.ftz.f32 %0, %1;" : "=f"(r) : "f"(v));
  return r;
}
__device__ __forceinline__ uint32_t exp_mufu(float a, float b) { return pack_bf(ex2(a), ex2(b)); }
__device__ __forceinline__ uint32_t exp_poly(float a, float b) {
  uint32_t w, t, p, r;
  asm("cvt.pack.sat.s16.s32 %0, %1, %2;" : "=r"(w) : "r"(__float_as_int(b)), "r"(__float_as_int(a)));
  const uint32_t u = w & 0x007F007Fu;
  asm("fma.rn.f16x2 %0, %1, %2, %3;" : "=r"(t) : "r"(u), "r"(0x79357935u), "r"(0x39593959u));
  asm("mul.rn.f16x2 %0, %1, %2;" : "=r"(p) : "r"(t), "r"(u));
  asm("lop3.b32 %0, %1, %2, %3, 0xEA;" : "=r"(r) : "r"(w), "r"(0xFF80FF80u), "r"(p));
  return r;
}
template <int BLO>
__device__ __forceinline__ void exp_half(const float (&s)[32], uint32_t (&p)[8]) {
#pragma unroll
  for (int b = BLO; b < BLO + 4; b++) {
    if ((POLY_PAT >> b) & 1) {
      p[2 * (b - BLO)] = exp_poly(s[4 * b], s[4 * b + 1]);
      p[2 * (b - BLO) + 1] = exp_poly(s[4 * b + 2], s[4 * b + 3]);
    } else {
      p[2 * (b - BLO)] = exp_mufu(s[4 * b], s[4 * b + 1]);
      p[2 * (b - BLO) + 1] = exp_mufu(s[4 * b + 2], s[4 * b + 3]);
    }
  }
}

__device__ __forceinline__ void mma16816(float (&c)[4], uint32_t a0, uint32_t a2, uint32_t b0, uint32_t b1) {
  asm volatile("mma.sync.aligned.m16n8k16.row.col.f32.bf16.bf16.f32 {%0,%1,%2,%3}, {%4,%5,%6,%5}, {%7,%8}, {%0,%1,%2,%3};"
               : "+f"(c[0]), "+f"(c[1]), "+f"(c[2]), "+f"(c[3]) : "r"(a0), "r"(0u), "r"(a2), "r"(b0), "r"(b1));
}
__device__ __forceinline__ void ldsm4t(uint32_t (&r)[4], uint32_t addr) {
  asm volatile("ldmatrix.sync.aligned.m8n8.x4.trans.shared.b16 {%0,%1,%2,%3}, [%4];"
               : "=r"(r[0]), "=r"(r[1]), "=r"(r[2]), "=r"(r[3]) : "r"(addr) : "memory");
}

constexpr int MOE_BOX = 128 * 128;
constexpr int MOE_SLOTS = 6, MOE_SLOT = 2 * MOE_BOX;

__device__ __noinline__ void moe_ffn(uint8_t* smem, int e, const __nv_bfloat16* __restrict__ x, const CUtensorMap* m_gate,
                                     const CUtensorMap* m_up, const CUtensorMap* m_down) {
  const int tid = threadIdx.x, lane = tid & 31, warp = __shfl_sync(0xffffffffu, tid >> 5, 0), g = lane >> 2, t = lane & 3;
  const uint32_t ring = (s2u(smem) + 1023) & ~1023u, bfull = ring + MOE_SLOTS * MOE_SLOT, bempty = bfull + 8 * MOE_SLOTS;
  __nv_bfloat16* xs = reinterpret_cast<__nv_bfloat16*>(smem + (ring - s2u(smem)) + MOE_SLOTS * MOE_SLOT + 128);
  __nv_bfloat16* hs = xs + 2 * D_;
  const int nblk = e == 3 ? 6 : 7, nchunk = e == 3 ? 3 : 4;
  const int nst1 = nblk * 5, nst = nst1 + nchunk * 5;
  __shared__ float s_val[16];
  __shared__ int s_idx[16];
  __shared__ int s_top[2];
  __shared__ float s_gate[2];
  __shared__ unsigned s_last;
  if (tid == 0) {
    for (int i = 0; i < MOE_SLOTS; i++) { mbar_init(bfull + 8 * i, 1); mbar_init(bempty + 8 * i, 8); }
    asm volatile("fence.mbarrier_init.release.cluster;" ::: "memory");
  }
  reinterpret_cast<uint32_t*>(hs)[tid] = 0u;
  __syncthreads();
  if (warp == 8) {
    if (lane == 0) {
      pdl_wait();
      for (const long long t0 = clock64(); clock64() - t0 < 5000;) {}
      for (int st = 0; st < nst; st++) {
        const int sl = st % MOE_SLOTS;
        if (st >= MOE_SLOTS) mbar_wait(bempty + 8 * sl, ((st / MOE_SLOTS) - 1) & 1);
        const uint32_t slot = ring + sl * MOE_SLOT, bar = bfull + 8 * sl;
        mbar_expect_tx(bar, MOE_SLOT);
        if (st < nst1) {
          tma2d(slot, m_gate, (e * 7 + st / 5) * 64, (st % 5) * 128, bar);
          tma2d(slot + MOE_BOX, m_up, (e * 7 + st / 5) * 64, (st % 5) * 128, bar);
        } else {
          const int u = st - nst1;
          tma2d(slot, m_down, (u % 5) * 128, e * 448 + (u / 5) * 128, bar);
          tma2d(slot + MOE_BOX, m_down, (u % 5) * 128 + 64, e * 448 + (u / 5) * 128, bar);
        }
      }
    }
    __syncwarp();
  }

  if (warp < 8) {
    float rv[8];
    unsigned long long pk[8];
#pragma unroll
    for (int i = 0; i < 8; i++) pk[i] = ld_packet(&g_rp[tid + 256 * i]);
#pragma unroll
    for (int i = 0; i < 8; i++)
      rv[i] = __uint_as_float((uint32_t)(pk[i] >> 32) == tag ? (uint32_t)pk[i] : get_packet(&g_rp[tid + 256 * i], tag));
    if (tid == 0) TL(1, 1);
    int first = -1;
    for (int pass = 0; pass < 2; pass++) {
      float bv = -INFINITY; int bi = 0x7fffffff;
#pragma unroll
      for (int i = 0; i < 8; i++) {
        const int idx = tid + 256 * i;
        if (idx != first && (rv[i] > bv || (rv[i] == bv && idx < bi))) { bv = rv[i]; bi = idx; }
      }
#pragma unroll
      for (int o = 16; o; o >>= 1) {
        const float ov = __shfl_xor_sync(0xffffffffu, bv, o);
        const int oi = __shfl_xor_sync(0xffffffffu, bi, o);
        if (ov > bv || (ov == bv && oi < bi)) { bv = ov; bi = oi; }
      }
      if (lane == 0) { s_val[warp] = bv; s_idx[warp] = bi; }
      bar_sync(1, 256);
      if (warp == 0) {
        float v = s_val[lane & 7]; int ix = s_idx[lane & 7];
#pragma unroll
        for (int o = 4; o; o >>= 1) {
          const float ov = __shfl_xor_sync(0xffffffffu, v, o);
          const int oi = __shfl_xor_sync(0xffffffffu, ix, o);
          if (ov > v || (ov == v && oi < ix)) { v = ov; ix = oi; }
        }
        if (lane == 0) {
          if (ix < 0 || ix >= S_) ix = pass;
          s_top[pass] = ix;
          s_gate[pass] = bf_round(1.0f / (1.0f + __expf(-v)));
          if (e == 0) g_idx[pass] = ix;
        }
      }
      bar_sync(1, 256);
      first = s_top[0];
    }
    for (int i = tid; i < 2 * D_; i += 256) {
      const int tok = i / D_, d = i % D_;
      const uint32_t st = get_packet(&g_stat[s_top[tok]], tag);
      const float m = __uint_as_float(st & 0xFFFF0000u), rstd = __fdiv_rn(1.0f, __uint_as_float(st << 16));
      reinterpret_cast<uint16_t*>(xs)[i] =
          (uint16_t)(__float_as_uint(bf_round(bf_round(__bfloat162float(x[s_top[tok] * D_ + d]) - m) * rstd)) >> 16);
    }
    bar_sync(1, 256);
    if (tid == 0) TL(1, 2);

    const uint32_t* xs32 = reinterpret_cast<const uint32_t*>(xs);
    int st = 0;
#pragma unroll 1
    for (int blk = 0; blk < nblk; blk++) {
      float cg[4] = {0.f, 0.f, 0.f, 0.f}, cu[4] = {0.f, 0.f, 0.f, 0.f};
#pragma unroll 1
      for (int kc = 0; kc < 5; kc++, st++) {
        const int sl = st % MOE_SLOTS;
        mbar_wait(bfull + 8 * sl, (st / MOE_SLOTS) & 1);
        const uint32_t base = ring + sl * MOE_SLOT + (lane >> 4) * MOE_BOX + (lane & 15) * 128 + ((warp ^ (lane & 7)) << 4);
#pragma unroll
        for (int ks = 0; ks < 8; ks++) {
          const int kw = kc * 64 + ks * 8 + t;
          const uint32_t a0 = g < 2 ? xs32[g * (D_ / 2) + kw] : 0u, a2 = g < 2 ? xs32[g * (D_ / 2) + kw + 4] : 0u;
          uint32_t b[4];
          ldsm4t(b, base + ks * 2048);
          mma16816(cg, a0, a2, b[0], b[1]);
          mma16816(cu, a0, a2, b[2], b[3]);
        }
        __syncwarp();
        if (lane == 0) mbar_arrive(bempty + 8 * sl);
      }
      if (g < 2) {
        float h[2];
#pragma unroll
        for (int i = 0; i < 2; i++) {
          const float gb = bf_round(cg[i]), ub = bf_round(cu[i]);
          h[i] = bf_round(gb / (1.0f + __expf(-gb))) * ub;
        }
        reinterpret_cast<uint32_t*>(hs)[g * 256 + blk * 32 + warp * 4 + t] = pack_bf(h[0], h[1]);
      }
    }
    bar_sync(1, 256);
    if (tid == 0) TL(1, 3);

    float cd[5][2][4];
#pragma unroll
    for (int q = 0; q < 5; q++)
#pragma unroll
      for (int i = 0; i < 4; i++) { cd[q][0][i] = 0.f; cd[q][1][i] = 0.f; }
    const uint32_t* hs32 = reinterpret_cast<const uint32_t*>(hs);
#pragma unroll 1
    for (int fc = 0; fc < nchunk; fc++) {
#pragma unroll
      for (int q = 0; q < 5; q++, st++) {
        const int sl = st % MOE_SLOTS;
        mbar_wait(bfull + 8 * sl, (st / MOE_SLOTS) & 1);
        const uint32_t base = ring + sl * MOE_SLOT + (lane >> 4) * MOE_BOX + (lane & 15) * 128 + ((warp ^ (lane & 7)) << 4);
#pragma unroll
        for (int ks = 0; ks < 8; ks++) {
          const int kw = fc * 64 + ks * 8 + t;
          const uint32_t a0 = g < 2 ? hs32[g * 256 + kw] : 0u, a2 = g < 2 ? hs32[g * 256 + kw + 4] : 0u;
          uint32_t b[4];
          ldsm4t(b, base + ks * 2048);
          mma16816(cd[q][0], a0, a2, b[0], b[1]);
          mma16816(cd[q][1], a0, a2, b[2], b[3]);
        }
        __syncwarp();
        if (lane == 0) mbar_arrive(bempty + 8 * sl);
      }
    }
    if (g < 2) {
#pragma unroll
      for (int q = 0; q < 5; q++)
#pragma unroll
        for (int b = 0; b < 2; b++)
          *reinterpret_cast<float2*>(&g_ypart[(e * 2 + g) * D_ + q * 128 + b * 64 + warp * 8 + 2 * t]) =
              make_float2(cd[q][b][0], cd[q][b][1]);
    }
  }
  __threadfence();
  __syncthreads();
  if (tid == 0) s_last = atomicAdd(&g_ffn_done, 1u) & 3u;
  __syncthreads();
  if (s_last == 3) {
    __threadfence();
    for (int i = tid; i < D_; i += K2_THREADS) {
      const int tok = i / (D_ / 2), d = 2 * (i % (D_ / 2));
      float s0 = 0.f, s1 = 0.f;
#pragma unroll
      for (int k = 0; k < 4; k++) {
        const float2 v = __ldcg(reinterpret_cast<const float2*>(&g_ypart[(k * 2 + tok) * D_ + d]));
        s0 += v.x; s1 += v.y;
      }
      g_upd[i] = pack_bf(bf_round(s0) * s_gate[tok], bf_round(s1) * s_gate[tok]);
    }
  }
}

__device__ __forceinline__ void attn_fallback(float (&o)[12], uint8_t* smem, uint32_t sK, uint32_t sV, uint32_t qoff, int wg,
                                              uint64_t dQ0, uint64_t dQ1) {
  const int tid = threadIdx.x & 127;
  uint16_t* q16 = reinterpret_cast<uint16_t*>(smem + qoff);
  for (int i = tid; i < 8 * 192; i += 128) {
    const int in = i % 192, slot = (in >> 6) * 8 + (in & 7);
    uint16_t* p = q16 + i;
    const bool cst = slot == 14 || slot == 15 || slot == 22 || slot == 23;
    const float v = cst ? 0.f : __uint_as_float((uint32_t)*p << 16) * 2361183241434822606848.0f;
    *p = (uint16_t)(__float_as_uint(v) >> 16);
  }
  fence_async_smem();
  bar_sync(1 + wg, 128);
  const uint64_t dK0 = mkdesc(sK, 128, 384, 0), dK1 = mkdesc(sK + 256, 0, 384, 0), dV = mkdesc(sV, 384, 128, 0);
  const float up = 2361183241434822606848.0f, down = 4.235164736271502e-22f;
  float m0 = -INFINITY, m1 = -INFINITY;
#pragma unroll
  for (int i = 0; i < 12; i++) o[i] = 0.f;
#pragma unroll 1
  for (int j = 0; j < 32; j++) {
    float s[32];
    uint32_t p[16];
    const uint64_t off = (uint64_t)(j * 192);
    WG_FENCE();
    mma_ss64<0>(s, dQ0, dK0 + off);
    mma_ss64<1>(s, dQ1, dK1 + off);
    WG_COMMIT();
    wg_wait<0>();
    pin(s);
    pin(o);
    float n0 = m0, n1 = m1;
#pragma unroll
    for (int b = 0; b < 8; b++) {
      const float f = ((POLY_PAT >> b) & 1) ? up : down;
      s[4 * b] *= f; s[4 * b + 1] *= f; s[4 * b + 2] *= f; s[4 * b + 3] *= f;
      n0 = fmaxf(n0, fmaxf(s[4 * b], s[4 * b + 1]));
      n1 = fmaxf(n1, fmaxf(s[4 * b + 2], s[4 * b + 3]));
    }
    n0 = fmaxf(n0, __shfl_xor_sync(0xffffffffu, n0, 1)); n0 = fmaxf(n0, __shfl_xor_sync(0xffffffffu, n0, 2));
    n1 = fmaxf(n1, __shfl_xor_sync(0xffffffffu, n1, 1)); n1 = fmaxf(n1, __shfl_xor_sync(0xffffffffu, n1, 2));
    const float c0 = exp2f(m0 - n0), c1 = exp2f(m1 - n1);
    m0 = n0; m1 = n1;
#pragma unroll
    for (int b = 0; b < 3; b++) { o[4 * b] *= c0; o[4 * b + 1] *= c0; o[4 * b + 2] *= c1; o[4 * b + 3] *= c1; }
#pragma unroll
    for (int b = 0; b < 8; b++) {
      p[2 * b] = exp_mufu(s[4 * b] - m0, s[4 * b + 1] - m0);
      p[2 * b + 1] = exp_mufu(s[4 * b + 2] - m1, s[4 * b + 3] - m1);
    }
    pin(o);
    pin(p);
    WG_FENCE();
#pragma unroll
    for (int k = 0; k < 4; k++) mma_pv(o, p[4 * k], p[4 * k + 1], p[4 * k + 2], p[4 * k + 3], dV + off + 48 * k);
    WG_COMMIT();
    wg_wait<0>();
    pin(o);
  }
}

__device__ __forceinline__ float2 store_shift(const float (&s)[32], uint8_t* qtile) {
  const int lane = threadIdx.x & 31, warp4 = (threadIdx.x >> 5) & 3, g = lane >> 2, t = lane & 3;
  float m0 = -INFINITY, m1 = -INFINITY, p0 = -INFINITY, p1 = -INFINITY;
#pragma unroll
  for (int b = 0; b < 8; b++) {
    if (!((POLY_PAT >> b) & 1)) {
      m0 = fmaxf(m0, fmaxf(s[4 * b], s[4 * b + 1]));
      m1 = fmaxf(m1, fmaxf(s[4 * b + 2], s[4 * b + 3]));
    } else {
      p0 = fmaxf(p0, fmaxf(s[4 * b], s[4 * b + 1]));
      p1 = fmaxf(p1, fmaxf(s[4 * b + 2], s[4 * b + 3]));
    }
  }
  const float k = 2361183241434822606848.0f;
  m0 = fmaxf(m0, p0 * k * k - 127.0f);
  m1 = fmaxf(m1, p1 * k * k - 127.0f);
  m0 = fmaxf(m0, __shfl_xor_sync(0xffffffffu, m0, 1)); m1 = fmaxf(m1, __shfl_xor_sync(0xffffffffu, m1, 1));
  m0 = fmaxf(m0, __shfl_xor_sync(0xffffffffu, m0, 2)); m1 = fmaxf(m1, __shfl_xor_sync(0xffffffffu, m1, 2));
  const float c0 = bf_round(m0 + 90.0f), c1 = bf_round(m1 + 90.0f);
  if (t == 0) {
    uint8_t* qp = qtile + (warp4 * 2) * 384 + 256 + g * 16 + 12;
    *reinterpret_cast<uint16_t*>(qp) = (uint16_t)(__float_as_uint(c0 * -5.421010862427522e-20f) >> 16);
    *reinterpret_cast<uint16_t*>(qp + 384) = (uint16_t)(__float_as_uint(c1 * -5.421010862427522e-20f) >> 16);
  }
  return make_float2(c0, c1);
}

__device__ __forceinline__ bool store_output(const float (&o)[12], __nv_bfloat16* __restrict__ orow) {
  const int lane = threadIdx.x & 31, warp4 = (threadIdx.x >> 5) & 3, g = lane >> 2, t = lane & 3;
  const float l0 = __shfl_sync(0xffffffffu, o[8], (lane & ~3) | 2);
  const float l1 = __shfl_sync(0xffffffffu, o[10], (lane & ~3) | 2);
  float i0, i1;
  asm("rcp.approx.ftz.f32 %0, %1;" : "=f"(i0) : "f"(l0));
  asm("rcp.approx.ftz.f32 %0, %1;" : "=f"(i1) : "f"(l1));
  uint32_t* dst0 = reinterpret_cast<uint32_t*>(orow + (warp4 * 16 + g) * D_) + t;
  uint32_t* dst1 = dst0 + 8 * (D_ / 2);
  dst0[0] = pack_bf(o[0] * i0, o[1] * i0);  dst1[0] = pack_bf(o[2] * i1, o[3] * i1);
  dst0[4] = pack_bf(o[4] * i0, o[5] * i0);  dst1[4] = pack_bf(o[6] * i1, o[7] * i1);
  if (t < 2) { dst0[8] = pack_bf(o[8] * i0, o[9] * i0); dst1[8] = pack_bf(o[10] * i1, o[11] * i1); }
  bool ok = l0 >= 7.888609052210118e-31f && l0 <= 1.0e37f && l1 >= 7.888609052210118e-31f && l1 <= 1.0e37f;
#pragma unroll
  for (int i = 0; i < 12; i++) ok = ok && fabsf(o[i]) <= 3.0e38f;
  return ok;
}

__global__ void __launch_bounds__(K2_THREADS, 1)
k2_attn(const __grid_constant__ CUtensorMap m_gate, const __grid_constant__ CUtensorMap m_up,
        const __grid_constant__ CUtensorMap m_down, const __nv_bfloat16* __restrict__ x) {
  extern __shared__ __align__(128) uint8_t smem[];
  const int tid = threadIdx.x;
  if (tid == 0) TL(1, 0);
  if (blockIdx.x < 4) {
    pdl_launch();
    moe_ffn(smem, blockIdx.x, x, &m_gate, &m_up, &m_down);
    if (tid == 0) TL(1, 5);
    return;
  }
  const int id = blockIdx.x - 4, head = id >> 2, qb = id & 3;
  const uint32_t sK = s2u(smem), sV = sK + K2_KV_BYTES, sQall = sV + K2_KV_BYTES, sZero = sQall + K2_Q_BYTES;
  const uint32_t bars = sZero + K2_ZERO_BYTES;
  if (tid == 0) {
    for (int i = 0; i < 6; i++) mbar_init(bars + 8 * i, 1);
    asm volatile("fence.mbarrier_init.release.cluster;" ::: "memory");
  }
  if (tid < K2_ZERO_BYTES / 16) reinterpret_cast<uint4*>(smem + 2 * K2_KV_BYTES + K2_Q_BYTES)[tid] = make_uint4(0, 0, 0, 0);
  fence_async_smem();
  __syncthreads();
  pdl_wait();
  pdl_launch();
  if (tid == 0) TL(1, 1);
  if (tid >= 497) g_cs[id * 15 + (tid - 497)] = 0ull;
  if (tid == 0) {
    const uint8_t* gq = reinterpret_cast<const uint8_t*>(g_qkv) + (size_t)head * HEAD_BYTES + qb * K2_Q_BYTES;
    const uint8_t* gk = reinterpret_cast<const uint8_t*>(g_qkv) + (size_t)(H_ + head) * HEAD_BYTES;
    const uint8_t* gv = gk + (size_t)H_ * HEAD_BYTES;
    mbar_expect_tx(bars + 40, K2_Q_BYTES + 6144);
    bulk_g2s(sK, gk, 6144, bars + 40);
    bulk_g2s(sQall, gq, K2_Q_BYTES, bars + 40);
    mbar_expect_tx(bars, 6144);
    bulk_g2s(sV, gv, 6144, bars);
    for (int c = 1; c < 5; c++) {
      const uint32_t off = 6144u << (c - 1), bytes = off;
      mbar_expect_tx(bars + 8 * c, 2 * bytes);
      bulk_g2s(sK + off, gk + off, bytes, bars + 8 * c);
      bulk_g2s(sV + off, gv + off, bytes, bars + 8 * c);
    }
  }
  const int wg = __reduce_max_sync(0xffffffffu, tid >> 7);
  __nv_bfloat16* orow = g_o + (qb * 512 + wg * 64) * D_ + head * 20;
  const uint64_t dK0 = mkdesc(sK, 128, 384, 0), dK1 = mkdesc(sK + 256, 0, 384, 0), dV = mkdesc(sV, 384, 128, 0);
  const uint32_t qoffA = 2 * K2_KV_BYTES + wg * 3072, qoffB = qoffA + 4 * 3072;
  const uint64_t dQA0 = mkdesc(sK + qoffA, 128, 384, 0), dQA1 = mkdesc(sK + qoffA + 256, sZero - (sK + qoffA + 256), 384, 0);
  const uint64_t dQB0 = mkdesc(sK + qoffB, 128, 384, 0), dQB1 = mkdesc(sK + qoffB + 256, sZero - (sK + qoffB + 256), 384, 0);
  float o[12];
  float s0[32], s1[32];
  uint32_t pa[8], pb[8];

#define QK(Sreg, Q0, Q1, OFF) do { mma_ss64<0>(Sreg, Q0, dK0 + (OFF)); mma_ss64<1>(Sreg, Q1, dK1 + (OFF)); } while (0)
#define PV(P, I, OFF) mma_pv(o, P[4 * (I)], P[4 * (I) + 1], P[4 * (I) + 2], P[4 * (I) + 3], dV + (OFF))
#define HALF_STEP(SA, SB, Q0, Q1, OFFP, OFFN)                               \
  WG_FENCE(); QK(SB, Q0, Q1, OFFN); WG_COMMIT();                            \
  exp_half<0>(SA, pa);                                                      \
  WG_FENCE(); PV(pa, 0, OFFP); PV(pa, 1, (OFFP) + 48); WG_COMMIT();         \
  wg_wait<2>();                                                             \
  exp_half<4>(SA, pb);                                                      \
  WG_FENCE(); PV(pb, 0, (OFFP) + 96); PV(pb, 1, (OFFP) + 144); WG_COMMIT(); \
  wg_wait<1>();                                                             \
  pin(SB);
#define LAST_STEPS(Q0, Q1)                                                  \
  {                                                                         \
    const uint64_t off = (uint64_t)(15 * 384);                              \
    HALF_STEP(s0, s1, Q0, Q1, off, off + 192)                               \
    exp_half<0>(s1, pa);                                                    \
    WG_FENCE(); PV(pa, 0, off + 192); PV(pa, 1, off + 240); WG_COMMIT();    \
    wg_wait<1>();                                                           \
    exp_half<4>(s1, pb);                                                    \
    WG_FENCE(); PV(pb, 0, off + 288); PV(pb, 1, off + 336); WG_COMMIT();    \
  }

  mbar_wait(bars + 40, 0);
  if (tid == 0) TL(1, 2);
  WG_FENCE(); QK(s0, dQA0, dQA1, 0); QK(s1, dQB0, dQB1, 0); WG_COMMIT();
  wg_wait<0>(); pin(s0); pin(s1);
  {
    const float2 c = store_shift(s0, smem + qoffA);
    store_shift(s1, smem + qoffB);
    fence_async_smem();
    const float k = 4.235164736271502e-22f;
    const float d0 = c.x * k * k, d1 = c.y * k * k;
#pragma unroll
    for (int b = 0; b < 8; b++) {
      const bool poly = (POLY_PAT >> b) & 1;
      s0[4 * b] -= poly ? d0 : c.x; s0[4 * b + 1] -= poly ? d0 : c.x;
      s0[4 * b + 2] -= poly ? d1 : c.y; s0[4 * b + 3] -= poly ? d1 : c.y;
    }
#pragma unroll
    for (int i = 0; i < 12; i++) o[i] = 0.f;
    pin(o);
    pin(s0);
    bar_sync(1 + wg, 128);
  }

  mbar_wait(bars, 0);
  if (tid == 0) TL(1, 6);
#pragma unroll 1
  for (int i = 0; i < 15; i++) {
    const uint64_t off = (uint64_t)(i * 384);
    const int in = i + 1;
    if ((in & (in - 1)) == 0) mbar_wait(bars + 8 * (32 - __clz(in)), 0);
    HALF_STEP(s0, s1, dQA0, dQA1, off, off + 192)
    HALF_STEP(s1, s0, dQA0, dQA1, off + 192, off + 384)
  }
  LAST_STEPS(dQA0, dQA1)
  WG_FENCE(); QK(s0, dQB0, dQB1, 0); WG_COMMIT();
  wg_wait<1>();
  pin(o);
  const bool okA = store_output(o, orow);
  if (tid == 0) TL(1, 3);

#pragma unroll
  for (int i = 0; i < 12; i++) o[i] = 0.f;
  pin(o);
  wg_wait<0>();
  pin(s0);
#pragma unroll 1
  for (int i = 0; i < 15; i++) {
    const uint64_t off = (uint64_t)(i * 384);
    HALF_STEP(s0, s1, dQB0, dQB1, off, off + 192)
    HALF_STEP(s1, s0, dQB0, dQB1, off + 192, off + 384)
  }
  LAST_STEPS(dQB0, dQB1)
  wg_wait<0>();
  pin(o);
  if (tid == 0) TL(1, 7);
  const bool okB = store_output(o, orow + 256 * D_);
  if (tid == 0) TL(1, 4);

  uint32_t bad;
  asm volatile("{\n.reg .pred p, q;\nsetp.eq.u32 p, %1, 0;\nbar.red.or.pred q, %2, 128, p;\nselp.u32 %0, 1, 0, q;\n}"
               : "=r"(bad) : "r"((uint32_t)(okA && okB)), "r"(1 + wg) : "memory");
  if (bad) {
#pragma unroll 1
    for (int task = 0; task < 2; task++) {
      attn_fallback(o, smem, sK, sV, task ? qoffB : qoffA, wg, task ? dQB0 : dQA0, task ? dQB1 : dQA1);
      store_output(o, orow + task * 256 * D_);
    }
  }
  if (tid == 0) TL(1, 5);
#undef QK
#undef PV
#undef HALF_STEP
#undef LAST_STEPS
}

constexpr int K3_THREADS = 288;
constexpr int K3_STAGES = 7;
constexpr int K3_B_BYTES = 80 * 640 * 2, K3_A_BYTES = 128 * 64 * 2;
constexpr int K3_SMEM = K3_STAGES * K3_A_BYTES + K3_B_BYTES + 1024 + 256;

__global__ void __launch_bounds__(K3_THREADS, 1)
k3_out(const __grid_constant__ CUtensorMap map_o, const __grid_constant__ CUtensorMap map_out,
       const __nv_bfloat16* __restrict__ x) {
  extern __shared__ uint8_t smem_raw[];
  const int tid = threadIdx.x, warp = __shfl_sync(0xffffffffu, tid >> 5, 0), lane = tid & 31;
  uint8_t* smem = smem_raw + (((s2u(smem_raw) + 1023) & ~1023u) - s2u(smem_raw));
  const uint32_t sbase = s2u(smem);
  const uint32_t sB = sbase + K3_STAGES * K3_A_BYTES;
  const uint32_t bar_full = sB + K3_B_BYTES, bar_empty = bar_full + 8 * K3_STAGES, bar_b = bar_empty + 8 * K3_STAGES;
  const int mb = blockIdx.x >> 3, nb = blockIdx.x & 7;
  if (tid == 0) TL(2, 0);
  if (warp == 8) {
    if (lane == 0) {
      asm volatile("prefetch.tensormap [%0];" ::"l"(&map_o) : "memory");
      asm volatile("prefetch.tensormap [%0];" ::"l"(&map_out) : "memory");
      for (int s = 0; s < K3_STAGES; s++) { mbar_init(bar_full + 8 * s, 1); mbar_init(bar_empty + 8 * s, 2); }
      mbar_init(bar_b, 1);
      asm volatile("fence.mbarrier_init.release.cluster;" ::: "memory");
    }
    __syncthreads();
    if (lane == 0) {
      mbar_expect_tx(bar_b, K3_B_BYTES);
      bulk_g2s(sB, reinterpret_cast<const uint8_t*>(g_wot) + (size_t)nb * K3_B_BYTES, K3_B_BYTES, bar_b);
      pdl_wait();
      TL(2, 1);
      for (int kc = 0; kc < 10; kc++) {
        const int s = kc % K3_STAGES;
        if (kc >= K3_STAGES) mbar_wait(bar_empty + 8 * s, 0);
        mbar_expect_tx(bar_full + 8 * s, K3_A_BYTES);
        tma2d(sbase + s * K3_A_BYTES, &map_o, kc * 64, mb * 128, bar_full + 8 * s);
      }

    }
    return;
  }
  const int wg = warp >> 2, g = lane >> 2, t = lane & 3;
  const int row = mb * 128 + wg * 64 + (warp & 3) * 16 + g;
  const int col = nb * 80 + 2 * t;
  uint32_t xr[20];
  float2 sp0 = make_float2(0.f, 1.f), sp1 = sp0;
#pragma unroll
  for (int j = 0; j < 20; j++) xr[j] = 0u;
  __syncthreads();
  float acc[40];
#pragma unroll
  for (int i = 0; i < 40; i++) acc[i] = 0.f;
  int i0 = -1, i1 = -1;
#pragma unroll 1
  for (int trip = 0; trip < 2; trip++) {
    const bool real = trip != 0;
    if (real) {
      sp0 = __ldcg(&g_statp[row]); sp1 = __ldcg(&g_statp[row + 8]);
#pragma unroll
      for (int j = 0; j < 10; j++) {
        xr[2 * j] = __ldg(reinterpret_cast<const uint32_t*>(x + row * D_ + col + 8 * j));
        xr[2 * j + 1] = __ldg(reinterpret_cast<const uint32_t*>(x + (row + 8) * D_ + col + 8 * j));
      }
      pdl_wait();
      if (tid < 16) { g_rp[blockIdx.x * 16 + tid] = 0ull; g_stat[blockIdx.x * 16 + tid] = 0ull; }
      i0 = __ldcg(&g_idx[0]); i1 = __ldcg(&g_idx[1]);
      mbar_wait(bar_b, 0);
#pragma unroll 1
      for (int kc = 0; kc < 10; kc++) {
        const int s = kc % K3_STAGES;
        mbar_wait(bar_full + 8 * s, (kc / K3_STAGES) & 1);
        if (tid == 0 && kc == 0) TL(2, 3);
        const uint64_t da = mkdesc(sbase + s * K3_A_BYTES + wg * 8192, 16, 1024, 1);
        const uint64_t db = mkdesc(sB + kc * 10240, 128, 1024, 0);
        WG_FENCE();
#pragma unroll
        for (int kk = 0; kk < 4; kk++) mma_ss80(acc, da + kk * 2, db + kk * 16, (kc | kk) != 0);
        WG_COMMIT();
        if (kc > 0) {
          wg_wait<1>();
          if ((tid & 127) == 0 && kc - 1 < 10 - K3_STAGES) mbar_arrive(bar_empty + 8 * (kc - 1));
        }
      }
      wg_wait<0>();
      pin(acc);
      if (tid == 0) TL(2, 4);
      bar_sync(1, 256);
    }
    const uint32_t stg = sB + ((wg * 64 + (warp & 3) * 16 + g) * 40 + t) * 4;
#pragma unroll
    for (int h = 0; h < 2; h++) {
      const float2 sp = h ? sp1 : sp0;
      const uint32_t m2 = pack_bf(sp.x, sp.x);
      uint32_t n[10];
#pragma unroll
      for (int j = 0; j < 10; j++) {
        const uint32_t d = bf2_sub(xr[2 * j + h], m2);
        n[j] = pack_bf(bf_lo(d) * sp.y, bf_hi(d) * sp.y);
      }
      const int r = row + 8 * h;
      if (r == i0 || r == i1) {
        const uint32_t* up = g_upd + (r == i0 ? 0 : D_ / 2) + (col >> 1);
#pragma unroll
        for (int j = 0; j < 10; j++) n[j] = bf2_add(n[j], __ldcg(up + 4 * j));
      }
#pragma unroll
      for (int j = 0; j < 10; j++) {
        const uint32_t a = bf2_add(xr[2 * j + h], pack_bf(acc[4 * j + 2 * h], acc[4 * j + 2 * h + 1]));
        sts_if(real, stg + (h * 320 + 4 * j) * 4, bf2_add(a, n[j]));
      }
    }
  }
  fence_async_smem();
  bar_sync(2 + wg, 128);
  if ((tid & 127) == 0) {
    asm volatile("cp.async.bulk.tensor.2d.global.shared::cta.bulk_group [%0, {%2, %3}], [%1];"
                 ::"l"(&map_out), "r"(sB + wg * 64 * 160), "r"(nb * 80), "r"(mb * 128 + wg * 64) : "memory");
    asm volatile("cp.async.bulk.commit_group;" ::: "memory");
    asm volatile("cp.async.bulk.wait_group.read 0;" ::: "memory");
  }
  if (tid == 0) TL(2, 5);
}

typedef CUresult (*EncodeFn)(CUtensorMap*, CUtensorMapDataType, cuuint32_t, void*, const cuuint64_t*, const cuuint64_t*,
                             const cuuint32_t*, const cuuint32_t*, CUtensorMapInterleave, CUtensorMapSwizzle,
                             CUtensorMapL2promotion, CUtensorMapFloatOOBfill);

CUtensorMap make_map_w(EncodeFn fn, const void* ptr, uint32_t nblk) {
  CUtensorMap m;
  const cuuint64_t dims[3] = {3 * D_, D_, nblk};
  const cuuint64_t strides[2] = {3 * D_ * 2, 128};
  const cuuint32_t box[3] = {64, 64, nblk};
  const cuuint32_t es[3] = {1, 1, 1};
  fn(&m, CU_TENSOR_MAP_DATA_TYPE_BFLOAT16, 3, const_cast<void*>(ptr), dims, strides, box, es, CU_TENSOR_MAP_INTERLEAVE_NONE,
     CU_TENSOR_MAP_SWIZZLE_128B, CU_TENSOR_MAP_L2_PROMOTION_L2_128B, CU_TENSOR_MAP_FLOAT_OOB_FILL_NONE);
  return m;
}

CUtensorMap make_map(EncodeFn fn, const void* ptr, uint64_t cols, uint64_t rows, uint32_t box_cols, uint32_t box_rows,
                     CUtensorMapSwizzle swz) {
  CUtensorMap m;
  const cuuint64_t dims[2] = {cols, rows};
  const cuuint64_t strides[1] = {cols * 2};
  const cuuint32_t box[2] = {box_cols, box_rows};
  const cuuint32_t es[2] = {1, 1};
  fn(&m, CU_TENSOR_MAP_DATA_TYPE_BFLOAT16, 2, const_cast<void*>(ptr), dims, strides, box, es, CU_TENSOR_MAP_INTERLEAVE_NONE,
     swz, CU_TENSOR_MAP_L2_PROMOTION_L2_128B, CU_TENSOR_MAP_FLOAT_OOB_FILL_NONE);
  return m;
}

}

extern "C" void kernel_launch(void* const* d_in, const int* in_sizes, int n_in, void* d_out, int out_size) {
  (void)in_sizes; (void)n_in; (void)out_size;
  const __nv_bfloat16* x = (const __nv_bfloat16*)d_in[0];
  const __nv_bfloat16* wqkv = (const __nv_bfloat16*)d_in[1];
  const __nv_bfloat16* wo = (const __nv_bfloat16*)d_in[2];
  const __nv_bfloat16* w_r = (const __nv_bfloat16*)d_in[4];
  const __nv_bfloat16* w_gate = (const __nv_bfloat16*)d_in[5];
  const __nv_bfloat16* w_up = (const __nv_bfloat16*)d_in[6];
  const __nv_bfloat16* w_down = (const __nv_bfloat16*)d_in[7];

  static EncodeFn encode = nullptr;
  static void* p_o = nullptr;
  if (!encode) {
    void* fn = nullptr;
    cudaDriverEntryPointQueryResult qr;
    cudaGetDriverEntryPoint("cuTensorMapEncodeTiled", &fn, cudaEnableDefault, &qr);
    encode = (EncodeFn)fn;
    cudaGetSymbolAddress(&p_o, g_o);
    cudaFuncSetAttribute(k1_ln_qkv, cudaFuncAttributeMaxDynamicSharedMemorySize, K1_SMEM);
    cudaFuncSetAttribute(k2_attn, cudaFuncAttributeMaxDynamicSharedMemorySize, K2_SMEM);
    cudaFuncSetAttribute(k3_out, cudaFuncAttributeMaxDynamicSharedMemorySize, K3_SMEM);
  }
  const CUtensorMap map_x = make_map(encode, x, D_, S_, 64, 128, CU_TENSOR_MAP_SWIZZLE_128B);
  const CUtensorMap map_w = make_map(encode, wqkv, 3 * D_, D_, 64, 64, CU_TENSOR_MAP_SWIZZLE_128B);
  const CUtensorMap map_w4 = make_map_w(encode, wqkv, 4), map_w3 = make_map_w(encode, wqkv, 3);
  const CUtensorMap map_o = make_map(encode, p_o, D_, S_, 64, 128, CU_TENSOR_MAP_SWIZZLE_128B);
  const CUtensorMap map_gate = make_map(encode, w_gate, F_, D_, 64, 128, CU_TENSOR_MAP_SWIZZLE_128B);
  const CUtensorMap map_up = make_map(encode, w_up, F_, D_, 64, 128, CU_TENSOR_MAP_SWIZZLE_128B);
  const CUtensorMap map_down = make_map(encode, w_down, D_, F_, 64, 128, CU_TENSOR_MAP_SWIZZLE_128B);
  const CUtensorMap map_out = make_map(encode, d_out, D_, S_, 80, 64, CU_TENSOR_MAP_SWIZZLE_NONE);

  cudaStream_t st = cudaStreamPerThread;
  k1_ln_qkv<<<128, K1_THREADS, K1_SMEM, st>>>(map_x, map_w, map_w4, map_w3, x, wqkv, w_r, wo);

  cudaLaunchAttribute at[1];
  at[0].id = cudaLaunchAttributeProgrammaticStreamSerialization;
  at[0].val.programmaticStreamSerializationAllowed = 1;
  cudaLaunchConfig_t cfg = {};
  cfg.stream = st;
  cfg.attrs = at;
  cfg.numAttrs = 1;
  cfg.gridDim = dim3(132); cfg.blockDim = dim3(K2_THREADS); cfg.dynamicSmemBytes = K2_SMEM;
  cudaLaunchKernelEx(&cfg, k2_attn, map_gate, map_up, map_down, x);
  cfg.gridDim = dim3(128); cfg.blockDim = dim3(K3_THREADS); cfg.dynamicSmemBytes = K3_SMEM;
  cudaLaunchKernelEx(&cfg, k3_out, map_o, map_out, x);
}
```

```cpp
#include <cuda_runtime.h>
#include <cuda_bf16.h>
#include <cuda.h>
#include <stdint.h>

namespace {

constexpr int S_ = 2048, D_ = 640, H_ = 32, F_ = 1728;

constexpr int HEAD_ELEMS = 256 * 192;
constexpr int HEAD_BYTES = HEAD_ELEMS * 2;
__device__ __align__(1024) __nv_bfloat16 g_o[S_ * D_];
__device__ __align__(1024) __nv_bfloat16 g_qkv[3 * H_ * HEAD_ELEMS];
__device__ __align__(1024) __nv_bfloat16 g_wot[D_ * D_];
__device__ unsigned long long g_rp[S_];
__device__ unsigned long long g_stat[S_];
__device__ unsigned long long g_cs[3 * D_];
__device__ float g_ypart[4 * 2 * D_];
__device__ uint32_t g_upd[D_];
__device__ int g_idx[2];
__device__ float2 g_statp[S_];
__device__ unsigned g_ffn_done;

constexpr unsigned POLY_PAT = 0xDAu;

__device__ __forceinline__ uint32_t s2u(const void* p) { return (uint32_t)__cvta_generic_to_shared(p); }
__device__ __forceinline__ void mbar_init(uint32_t bar, uint32_t cnt) {
  asm volatile("mbarrier.init.shared::cta.b64 [%0], %1;" ::"r"(bar), "r"(cnt) : "memory");
}
__device__ __forceinline__ void mbar_expect_tx(uint32_t bar, uint32_t bytes) {
  asm volatile("mbarrier.arrive.expect_tx.shared::cta.b64 _, [%0], %1;" ::"r"(bar), "r"(bytes) : "memory");
}
__device__ __forceinline__ void mbar_arrive(uint32_t bar) {
  asm volatile("mbarrier.arrive.shared::cta.b64 _, [%0];" ::"r"(bar) : "memory");
}
__device__ __forceinline__ bool mbar_try(uint32_t bar, uint32_t parity) {
  uint32_t ok;
  asm volatile("{\n.reg .pred p;\nmbarrier.try_wait.parity.shared::cta.b64 p, [%1], %2;\nselp.u32 %0, 1, 0, p;\n}"
               : "=r"(ok) : "r"(bar), "r"(parity) : "memory");
  return ok != 0;
}
__device__ __forceinline__ void mbar_wait(uint32_t bar, uint32_t parity) {
  if (mbar_try(bar, parity)) return;
  for (int it = 0; !mbar_try(bar, parity); ++it)
    if (it > (1 << 22)) __trap();
}
__device__ __forceinline__ void bulk_g2s(uint32_t dst, const void* src, uint32_t bytes, uint32_t bar) {
  asm volatile("cp.async.bulk.shared::cluster.global.mbarrier::complete_tx::bytes [%0], [%1], %2, [%3];"
               ::"r"(dst), "l"(src), "r"(bytes), "r"(bar) : "memory");
}
__device__ __forceinline__ void tma2d(uint32_t dst, const CUtensorMap* map, int c0, int c1, uint32_t bar) {
  asm volatile("cp.async.bulk.tensor.2d.shared::cluster.global.mbarrier::complete_tx::bytes [%0], [%1, {%3, %4}], [%2];"
               ::"r"(dst), "l"(map), "r"(bar), "r"(c0), "r"(c1) : "memory");
}
__device__ __forceinline__ void tma3d(uint32_t dst, const CUtensorMap* map, int c0, int c1, int c2, uint32_t bar) {
  asm volatile("cp.async.bulk.tensor.3d.shared::cluster.global.mbarrier::complete_tx::bytes [%0], [%1, {%3, %4, %5}], [%2];"
               ::"r"(dst), "l"(map), "r"(bar), "r"(c0), "r"(c1), "r"(c2) : "memory");
}
__device__ __forceinline__ void pdl_launch() { asm volatile("griddepcontrol.launch_dependents;" ::: "memory"); }
__device__ __forceinline__ void pdl_wait() { asm volatile("griddepcontrol.wait;" ::: "memory"); }
__device__ __forceinline__ void fence_async_smem() { asm volatile("fence.proxy.async.shared::cta;" ::: "memory"); }
__device__ __forceinline__ void bar_sync(int id, int n) { asm volatile("bar.sync %0, %1;" ::"r"(id), "r"(n) : "memory"); }
constexpr uint32_t tag = 1;
__device__ __forceinline__ void put_packet(unsigned long long* p, uint32_t payload, uint32_t tag_) {
  asm volatile("st.relaxed.gpu.global.b64 [%0], %1;" ::"l"(p), "l"(((unsigned long long)tag_ << 32) | payload) : "memory");
}
__device__ __forceinline__ unsigned long long ld_packet(const unsigned long long* p) {
  unsigned long long v;
  asm volatile("ld.relaxed.gpu.global.b64 %0, [%1];" : "=l"(v) : "l"(p) : "memory");
  return v;
}
__device__ __forceinline__ uint32_t get_packet(const unsigned long long* p, uint32_t tag_) {
  unsigned long long v = ld_packet(p);
  for (int it = 0; (uint32_t)(v >> 32) != tag_; ++it) {
    if (it > (1 << 22)) __trap();
    v = ld_packet(p);
  }
  return (uint32_t)v;
}

#define WG_FENCE() asm volatile("wgmma.fence.sync.aligned;" ::: "memory")
#define WG_COMMIT() asm volatile("wgmma.commit_group.sync.aligned;" ::: "memory")
template <int N> __device__ __forceinline__ void wg_wait() {
  asm volatile("wgmma.wait_group.sync.aligned %0;" ::"n"(N) : "memory");
}
template <int N> __device__ __forceinline__ void pin(float (&d)[N]) {
#pragma unroll
  for (int i = 0; i < N; i++) asm volatile("" : "+f"(d[i])::"memory");
}
template <int N> __device__ __forceinline__ void pin(uint32_t (&d)[N]) {
#pragma unroll
  for (int i = 0; i < N; i++) asm volatile("" : "+r"(d[i])::"memory");
}
__device__ __forceinline__ uint64_t mkdesc(uint32_t addr, uint32_t lbo, uint32_t sbo, uint32_t swz) {
  return (uint64_t)((addr & 0x3FFFF) >> 4) | ((uint64_t)(lbo >> 4) << 16) | ((uint64_t)(sbo >> 4) << 32) |
         ((uint64_t)swz << 62);
}

#define R4(d, i) "+f"(d[i]), "+f"(d[i + 1]), "+f"(d[i + 2]), "+f"(d[i + 3])
#define R8(d, i) R4(d, i), R4(d, i + 4)
#define R16(d, i) R8(d, i), R8(d, i + 8)
#define R32(d, i) R16(d, i), R16(d, i + 16)

template <int ACC> __device__ __forceinline__ void mma_ss64(float (&d)[32], uint64_t da, uint64_t db) {
  asm volatile(
      "wgmma.mma_async.sync.aligned.m64n64k16.f32.bf16.bf16 "
      "{%0,%1,%2,%3,%4,%5,%6,%7,%8,%9,%10,%11,%12,%13,%14,%15,%16,%17,%18,%19,%20,%21,%22,%23,%24,%25,%26,%27,%28,%29,%30,%31},"
      "%32, %33, %34, 1, 1, 0, 0;"
      : R32(d, 0) : "l"(da), "l"(db), "n"(ACC));
}
__device__ __forceinline__ void mma_pv(float (&d)[12], uint32_t a0, uint32_t a1, uint32_t a2, uint32_t a3, uint64_t db) {
  asm volatile(
      "wgmma.mma_async.sync.aligned.m64n24k16.f32.bf16.bf16 "
      "{%0,%1,%2,%3,%4,%5,%6,%7,%8,%9,%10,%11}, {%12,%13,%14,%15}, %16, 1, 1, 1, 1;"
      : R8(d, 0), R4(d, 8) : "r"(a0), "r"(a1), "r"(a2), "r"(a3), "l"(db));
}
__device__ __forceinline__ void mma_ss240(float (&d)[120], uint64_t da, uint64_t db, int acc) {
  asm volatile(
      "{\n.reg .pred p;\nsetp.ne.b32 p, %122, 0;\n"
      "wgmma.mma_async.sync.aligned.m64n240k16.f32.bf16.bf16 "
      "{%0,%1,%2,%3,%4,%5,%6,%7,%8,%9,%10,%11,%12,%13,%14,%15,%16,%17,%18,%19,%20,%21,%22,%23,%24,%25,%26,%27,%28,%29,"
      "%30,%31,%32,%33,%34,%35,%36,%37,%38,%39,%40,%41,%42,%43,%44,%45,%46,%47,%48,%49,%50,%51,%52,%53,%54,%55,%56,%57,%58,%59,"
      "%60,%61,%62,%63,%64,%65,%66,%67,%68,%69,%70,%71,%72,%73,%74,%75,%76,%77,%78,%79,%80,%81,%82,%83,%84,%85,%86,%87,%88,%89,"
      "%90,%91,%92,%93,%94,%95,%96,%97,%98,%99,%100,%101,%102,%103,%104,%105,%106,%107,%108,%109,%110,%111,%112,%113,%114,%115,%116,%117,%118,%119},"
      "%120, %121, p, 1, 1, 0, 1;\n}"
      : R32(d, 0), R32(d, 32), R32(d, 64), R16(d, 96), R8(d, 112)
      : "l"(da), "l"(db), "r"(acc));
}
__device__ __forceinline__ void mma_ss80(float (&d)[40], uint64_t da, uint64_t db, int acc) {
  asm volatile(
      "{\n.reg .pred p;\nsetp.ne.b32 p, %42, 0;\n"
      "wgmma.mma_async.sync.aligned.m64n80k16.f32.bf16.bf16 "
      "{%0,%1,%2,%3,%4,%5,%6,%7,%8,%9,%10,%11,%12,%13,%14,%15,%16,%17,%18,%19,%20,%21,%22,%23,%24,%25,%26,%27,%28,%29,"
      "%30,%31,%32,%33,%34,%35,%36,%37,%38,%39},"
      "%40, %41, p, 1, 1, 0, 1;\n}"
      : R32(d, 0), R8(d, 32)
      : "l"(da), "l"(db), "r"(acc));
}

__device__ __forceinline__ void sts(uint32_t addr, uint32_t v) { asm volatile("st.shared.b32 [%0], %1;" ::"r"(addr), "r"(v)); }
__device__ __forceinline__ void sts_if(bool p, uint32_t addr, uint32_t v) {
  asm volatile("{\n.reg .pred p;\nsetp.ne.u32 p, %2, 0;\n@p st.shared.b32 [%0], %1;\n}" ::"r"(addr), "r"(v), "r"((uint32_t)p));
}
__device__ __forceinline__ float bf_round(float v) {
  uint32_t r;
  asm("cvt.rn.bf16x2.f32 %0, %1, %2;" : "=r"(r) : "f"(v), "f"(0.0f));
  return __uint_as_float(r);
}
__device__ __forceinline__ uint32_t pack_bf(float lo, float hi) {
  uint32_t r;
  asm("cvt.rn.bf16x2.f32 %0, %1, %2;" : "=r"(r) : "f"(hi), "f"(lo));
  return r;
}
__device__ __forceinline__ uint32_t bf2_add(uint32_t a, uint32_t b) {
  uint32_t r;
  asm("add.rn.bf16x2 %0, %1, %2;" : "=r"(r) : "r"(a), "r"(b));
  return r;
}
__device__ __forceinline__ uint32_t bf2_sub(uint32_t a, uint32_t b) {
  uint32_t r;
  asm("sub.rn.bf16x2 %0, %1, %2;" : "=r"(r) : "r"(a), "r"(b));
  return r;
}
__device__ __forceinline__ float bf_lo(uint32_t u) { return __uint_as_float(u << 16); }
__device__ __forceinline__ float bf_hi(uint32_t u) { return __uint_as_float(u & 0xFFFF0000u); }

constexpr int K1_THREADS = 384;
constexpr int K1_STAGES = 4;
constexpr int K1_A_BYTES = 128 * 64 * 2, K1_B_BYTES = 4 * 64 * 64 * 2, K1_STAGE = K1_A_BYTES + K1_B_BYTES;
constexpr int K1_AUX = K1_STAGES * K1_STAGE;
constexpr int K1_SMEM = K1_AUX + 128 + 1024 + 1024 + 3072 + 1024;

__device__ __forceinline__ void ln_stats2(const uint2 (&xa)[5], const uint2 (&xb)[5], const uint2 (&wv)[5], int row, int lane) {
  float s[2] = {0.f, 0.f}, q[2] = {0.f, 0.f}, tw[2] = {0.f, 0.f}, x0[2], sw = 0.f;
  x0[0] = bf_lo(__shfl_sync(~0u, xa[0].x, 0));
  x0[1] = bf_lo(__shfl_sync(~0u, xb[0].x, 0));
#pragma unroll
  for (int i = 0; i < 5; i++) {
    const uint2 w = wv[i];
    const float w0 = bf_lo(w.x), w1 = bf_hi(w.x), w2 = bf_lo(w.y), w3 = bf_hi(w.y);
    sw += (w0 + w1) + (w2 + w3);
#pragma unroll
    for (int r = 0; r < 2; r++) {
      const uint2 u = r ? xb[i] : xa[i];
      const float d0 = bf_lo(u.x) - x0[r], d1 = bf_hi(u.x) - x0[r], d2 = bf_lo(u.y) - x0[r], d3 = bf_hi(u.y) - x0[r];
      s[r] += (d0 + d1) + (d2 + d3);
      q[r] = fmaf(d0, d0, fmaf(d1, d1, fmaf(d2, d2, fmaf(d3, d3, q[r]))));
      tw[r] = fmaf(d0, w0, fmaf(d1, w1, fmaf(d2, w2, fmaf(d3, w3, tw[r]))));
    }
  }
#pragma unroll
  for (int o = 16; o; o >>= 1) {
    s[0] += __shfl_xor_sync(~0u, s[0], o); q[0] += __shfl_xor_sync(~0u, q[0], o); tw[0] += __shfl_xor_sync(~0u, tw[0], o);
    s[1] += __shfl_xor_sync(~0u, s[1], o); q[1] += __shfl_xor_sync(~0u, q[1], o); tw[1] += __shfl_xor_sync(~0u, tw[1], o);
    sw += __shfl_xor_sync(~0u, sw, o);
  }
  const bool second = lane & 1;
  const float xs = second ? x0[1] : x0[0];
  const float md = (second ? s[1] : s[0]) * (1.0f / D_);
  const float var = fmaxf(fmaf(-md, md, (second ? q[1] : q[0]) * (1.0f / D_)), 0.f);
  const float m = bf_round(md + xs);
  const float den = bf_round(__fsqrt_rn(bf_round(bf_round(var) + 1e-5f)));
  if (lane < 2) {
    const uint32_t pay = __float_as_uint(m) | (__float_as_uint(den) >> 16);
    put_packet(&g_stat[row + lane], pay, tag);
    g_statp[row + lane] = make_float2(m, __fdiv_rn(1.0f, den));
    const float r = __fdiv_rn(fmaf(xs - m, sw, second ? tw[1] : tw[0]), den);
    put_packet(&g_rp[row + lane], __float_as_uint(bf_round(r)), tag);
  }
}

__device__ __forceinline__ void k1_store_duty(uint32_t sbase, int warp, int lane, int mb, int nb) {
#pragma unroll 1
  for (int ev = 0; ev < 6; ev++) {
    bar_sync(3 + ev, 256);
    if (lane == 0) {
      const int hl = 4 * (ev >> 1) + (warp - 8), wg = ev & 1;
      uint8_t* dst = reinterpret_cast<uint8_t*>(g_qkv) + (size_t)(nb * 12 + hl) * HEAD_BYTES + mb * 6144 + wg * 3072;
      asm volatile("cp.async.bulk.global.shared::cta.bulk_group [%0], [%1], 3072;"
                   ::"l"(dst), "r"(sbase + hl * 6144 + wg * 3072) : "memory");
      asm volatile("cp.async.bulk.commit_group;" ::: "memory");
    }
  }
  if (lane == 0) asm volatile("cp.async.bulk.wait_group.read 0;" ::: "memory");
}

__global__ void __launch_bounds__(K1_THREADS, 1)
k1_ln_qkv(const __grid_constant__ CUtensorMap map_x, const __grid_constant__ CUtensorMap map_w,
          const __grid_constant__ CUtensorMap map_w4, const __grid_constant__ CUtensorMap map_w3,
          const __nv_bfloat16* __restrict__ x, const __nv_bfloat16* __restrict__ wqkv,
          const __nv_bfloat16* __restrict__ w_r, const __nv_bfloat16* __restrict__ wo) {
  extern __shared__ uint8_t smem_raw[];
  const int tid = threadIdx.x, warp = __shfl_sync(0xffffffffu, tid >> 5, 0), lane = tid & 31;
  const int bid = blockIdx.x;
  uint8_t* smem = smem_raw + (((s2u(smem_raw) + 1023) & ~1023u) - s2u(smem_raw));
  const uint32_t sbase = s2u(smem);
  const uint32_t bar_full = sbase + K1_AUX, bar_empty = bar_full + 8 * K1_STAGES;
  float2* s_stat = reinterpret_cast<float2*>(smem + K1_AUX + 128);
  float* s_cs = reinterpret_cast<float*>(smem + K1_AUX + 128 + 1024);
  const int mb = bid & 15, nb = bid >> 4;

  if (tid == 256) {
    asm volatile("prefetch.tensormap [%0];" ::"l"(&map_x) : "memory");
    asm volatile("prefetch.tensormap [%0];" ::"l"(nb < 7 ? &map_w4 : &map_w3) : "memory");
    for (int s = 0; s < K1_STAGES; s++) { mbar_init(bar_full + 8 * s, 1); mbar_init(bar_empty + 8 * s, 2); }
    asm volatile("fence.mbarrier_init.release.cluster;" ::: "memory");
  }
  __syncthreads();
  pdl_launch();

  if (warp == 8) {
    if (lane == 0) {
      for (int kc = 0; kc < 10; kc++) {
        const int s = kc % K1_STAGES;
        if (kc >= K1_STAGES) mbar_wait(bar_empty + 8 * s, ((kc / K1_STAGES) - 1) & 1);
        mbar_expect_tx(bar_full + 8 * s, K1_STAGE);
        const uint32_t sa = sbase + s * K1_STAGE, sb = sa + K1_A_BYTES;
        tma3d(sb, nb < 7 ? &map_w4 : &map_w3, nb * 240, kc * 64, 0, bar_full + 8 * s);
        if (nb == 7) tma2d(sb + 3 * 8192, &map_w, nb * 240 + 192, kc * 64, bar_full + 8 * s);
        tma2d(sa, &map_x, kc * 64, mb * 128, bar_full + 8 * s);
      }
    }
    __syncwarp();
    k1_store_duty(sbase, warp, lane, mb, nb);
    return;
  }

  if (warp > 8) {
    const int at = tid - 288;
    float* s_part = reinterpret_cast<float*>(smem + K1_AUX + 128 + 2048);
    mbar_wait(bar_full, 0);
    if (mb < 15) {
      const int half = at & 1, rg = at >> 1;
      const uint4* wp = reinterpret_cast<const uint4*>(wqkv + (size_t)rg * (3 * D_) + nb * 240 + mb * 16) + half;
      uint4 v[14];
#pragma unroll
      for (int k = 0; k < 14; k++)
        v[k] = (rg + 48 * k < D_) ? __ldg(wp + (size_t)k * 48 * (3 * D_ / 8)) : make_uint4(0, 0, 0, 0);
      float c[8];
#pragma unroll
      for (int i = 0; i < 8; i++) c[i] = 0.f;
#pragma unroll
      for (int k = 0; k < 14; k++) {
        c[0] += bf_lo(v[k].x); c[1] += bf_hi(v[k].x); c[2] += bf_lo(v[k].y); c[3] += bf_hi(v[k].y);
        c[4] += bf_lo(v[k].z); c[5] += bf_hi(v[k].z); c[6] += bf_lo(v[k].w); c[7] += bf_hi(v[k].w);
      }
#pragma unroll
      for (int o = 2; o < 32; o <<= 1)
#pragma unroll
        for (int i = 0; i < 8; i++) c[i] += __shfl_xor_sync(0xffffffffu, c[i], o);
      if (lane < 2) {
#pragma unroll
        for (int i = 0; i < 8; i++) s_part[(warp - 9) * 16 + lane * 8 + i] = c[i];
      }
      bar_sync(1, 96);
      if (at < 16)
        put_packet(&g_cs[nb * 240 + mb * 16 + at], __float_as_uint(s_part[at] + s_part[16 + at] + s_part[32 + at]), tag);
    }
    uint4 wov[5];
#pragma unroll
    for (int i = 0; i < 5; i++) {
      const int j = at + 96 * i;
      if (j < 400) wov[i] = __ldg(reinterpret_cast<const uint4*>(wo) + bid * 400 + j);
    }
    {
      const unsigned long long* ps = &g_stat[mb * 128 + at];
      const unsigned long long* pc = &g_cs[nb * 240 + at];
      unsigned long long v0, v1, c0, c1, c2;
      for (int it = 0;; ++it) {
        v0 = ld_packet(ps);
        v1 = at < 32 ? ld_packet(ps + 96) : (1ull << 32);
        c0 = ld_packet(pc);
        c1 = ld_packet(pc + 96);
        c2 = at < 48 ? ld_packet(pc + 192) : (1ull << 32);
        if (((uint32_t)(v0 >> 32) & (uint32_t)(v1 >> 32) & (uint32_t)(c0 >> 32) & (uint32_t)(c1 >> 32) & (uint32_t)(c2 >> 32)) == tag) break;
        if (it > (1 << 22)) __trap();
      }
      s_stat[at] = make_float2(__uint_as_float((uint32_t)v0 & 0xFFFF0000u), __fdiv_rn(1.0f, __uint_as_float((uint32_t)v0 << 16)));
      if (at < 32)
        s_stat[96 + at] = make_float2(__uint_as_float((uint32_t)v1 & 0xFFFF0000u), __fdiv_rn(1.0f, __uint_as_float((uint32_t)v1 << 16)));
      s_cs[at] = __uint_as_float((uint32_t)c0);
      s_cs[96 + at] = __uint_as_float((uint32_t)c1);
      if (at < 48) s_cs[192 + at] = __uint_as_float((uint32_t)c2);
    }
    __threadfence_block();
    asm volatile("bar.arrive 2, 352;" ::: "memory");
#pragma unroll
    for (int i = 0; i < 5; i++) {
      const int j = at + 96 * i;
      if (j < 400) {
        const int li = bid * 400 + j, k = li / 80, cv = li % 80;
        const int dst = ((((cv / 10) * 10 + (k >> 6)) * 10 + (cv % 10)) * 8 + ((k >> 3) & 7)) * 8 + (k & 7);
        reinterpret_cast<uint4*>(g_wot)[dst] = wov[i];
      }
    }
    k1_store_duty(sbase, warp, lane, mb, nb);
    return;
  }

  const int wg = warp >> 2;
  const int lrow = mb * 128 + nb * 16 + warp * 2;
  uint2 xa[5], xb[5], wv[5];
#pragma unroll
  for (int i = 0; i < 5; i++) {
    xa[i] = __ldg(reinterpret_cast<const uint2*>(x + lrow * D_) + i * 32 + lane);
    xb[i] = __ldg(reinterpret_cast<const uint2*>(x + (lrow + 1) * D_) + i * 32 + lane);
    wv[i] = __ldg(reinterpret_cast<const uint2*>(w_r) + i * 32 + lane);
  }
  ln_stats2(xa, xb, wv, lrow, lane);

  float acc[120];
#pragma unroll 1
  for (int kc = 0; kc < 10; kc++) {
    const int s = kc % K1_STAGES;
    mbar_wait(bar_full + 8 * s, (kc / K1_STAGES) & 1);
    const uint32_t sa = sbase + s * K1_STAGE + wg * 8192, sb = sbase + s * K1_STAGE + K1_A_BYTES;
    const uint64_t da = mkdesc(sa, 16, 1024, 1), db = mkdesc(sb, 8192, 1024, 1);
    WG_FENCE();
#pragma unroll
    for (int kk = 0; kk < 4; kk++) mma_ss240(acc, da + kk * 2, db + kk * 128, (kc | kk) != 0);
    WG_COMMIT();
    if (kc > 0) {
      wg_wait<1>();
      if ((tid & 127) == 0 && kc - 1 + K1_STAGES < 10) mbar_arrive(bar_empty + 8 * ((kc - 1) % K1_STAGES));
    }
  }
  wg_wait<0>();
  pin(acc);
  bar_sync(2, 352);

  const int g = lane >> 2, t = lane & 3;
  const int rl = wg * 64 + (warp & 3) * 16 + g;
  const int grp = rl >> 3;
  const bool poly0 = (POLY_PAT >> (grp & 7)) & 1, poly1 = (POLY_PAT >> ((grp + 1) & 7)) & 1;
  const float qs = 0.22360679774997896f * 1.4426950408889634f * 5.421010862427522e-20f;
  const float kbig = 18446744073709551616.0f, ksmall = 3.308722450212111e-24f;
  const float2 st0 = s_stat[rl], st1 = s_stat[rl + 8];
  const float nm0 = -st0.x, nm1 = -st1.x;
  constexpr int HS = 1536;
  const uint32_t gb = sbase + (grp * 96 + g * 4) * 4;
  const float* const csp = s_cs + 2 * t;
#pragma unroll
  for (int bt = 0; bt < 3; bt++) {
    const int type = (nb * 12 + 4 * bt) >> 5;
    const bool isv = type == 2;
    const float s0 = st0.y * (type == 0 ? qs : (isv ? 1.0f : (poly0 ? ksmall : kbig)));
    const float s1 = st1.y * (type == 0 ? qs : (isv ? 1.0f : (poly1 ? ksmall : kbig)));
    const uint32_t hb = gb + 4 * bt * HS * 4;
    uint32_t p[5];
    p[0] = hb + 4 * t;
    p[1] = hb + 4 * ((t == 3 && !isv) ? 64 : 32 + t);
    p[2] = hb + 4 * (t < 2 ? 64 + t + (isv ? 0 : 1) : HS + t - 2);
    p[3] = hb + 4 * (t < 2 ? 2 + t : 30 + t);
    p[4] = hb + 4 * (t == 0 ? 34 : (isv ? (t == 1 ? 35 : 62 + t) : 63 + t));
    float2 csv[10];
#pragma unroll
    for (int jj = 0; jj < 10; jj++) csv[jj] = *reinterpret_cast<const float2*>(csp + 8 * (10 * bt + jj));
#pragma unroll
    for (int jj = 0; jj < 10; jj++) {
      const int j = 10 * bt + jj;
      const int h0 = (8 * jj) / 20;
      const float2 cs = csv[jj];
      const uint32_t q = p[jj % 5] + h0 * HS * 4;
      sts(q, pack_bf(fmaf(nm0, cs.x, acc[4 * j]) * s0, fmaf(nm0, cs.y, acc[4 * j + 1]) * s0));
      sts(q + 384, pack_bf(fmaf(nm1, cs.x, acc[4 * j + 2]) * s1, fmaf(nm1, cs.y, acc[4 * j + 3]) * s1));
    }
    const uint32_t cb = hb + t * HS * 4;
    const uint32_t a0 = type == 0 ? 0x00001F80u : (isv ? 0x00003F80u : (poly0 ? 0x00001E00u : 0u));
    const uint32_t a1 = type == 0 ? 0x00001F80u : (isv ? 0x00003F80u : (poly1 ? 0x00001E00u : 0u));
    const uint32_t b0 = type == 0 ? 0x1F800000u : (isv ? 0u : (poly0 ? 0x987E1880u : 0x64F05F80u));
    const uint32_t b1 = type == 0 ? 0x1F800000u : (isv ? 0u : (poly1 ? 0x987E1880u : 0x64F05F80u));
    sts(cb + (isv ? 66 : 35) * 4, a0); sts(cb + 384 + (isv ? 66 : 35) * 4, a1);
    sts(cb + 67 * 4, b0); sts(cb + 384 + 67 * 4, b1);
    fence_async_smem();
    asm volatile("bar.arrive %0, 256;" ::"r"(3 + 2 * bt + wg) : "memory");
  }
}

constexpr int K2_THREADS = 512;
constexpr int K2_KV_BYTES = 98304, K2_Q_BYTES = 24576, K2_ZERO_BYTES = 2816;
constexpr int K2_SMEM = 2 * K2_KV_BYTES + K2_Q_BYTES + K2_ZERO_BYTES + 256;

__device__ __forceinline__ float ex2(float v) {
  float r;
  asm("ex2.approx.ftz.f32 %0, %1;" : "=f"(r) : "f"(v));
  return r;
}
__device__ __forceinline__ uint32_t exp_mufu(float a, float b) { return pack_bf(ex2(a), ex2(b)); }
__device__ __forceinline__ uint32_t exp_poly(float a, float b) {
  uint32_t w, t, p, r;
  asm("cvt.pack.sat.s16.s32 %0, %1, %2;" : "=r"(w) : "r"(__float_as_int(b)), "r"(__float_as_int(a)));
  const uint32_t u = w & 0x007F007Fu;
  asm("fma.rn.f16x2 %0, %1, %2, %3;" : "=r"(t) : "r"(u), "r"(0x79357935u), "r"(0x39593959u));
  asm("mul.rn.f16x2 %0, %1, %2;" : "=r"(p) : "r"(t), "r"(u));
  asm("lop3.b32 %0, %1, %2, %3, 0xEA;" : "=r"(r) : "r"(w), "r"(0xFF80FF80u), "r"(p));
  return r;
}
template <int BLO>
__device__ __forceinline__ void exp_half(const float (&s)[32], uint32_t (&p)[8]) {
#pragma unroll
  for (int b = BLO; b < BLO + 4; b++) {
    if ((POLY_PAT >> b) & 1) {
      p[2 * (b - BLO)] = exp_poly(s[4 * b], s[4 * b + 1]);
      p[2 * (b - BLO) + 1] = exp_poly(s[4 * b + 2], s[4 * b + 3]);
    } else {
      p[2 * (b - BLO)] = exp_mufu(s[4 * b], s[4 * b + 1]);
      p[2 * (b - BLO) + 1] = exp_mufu(s[4 * b + 2], s[4 * b + 3]);
    }
  }
}

__device__ __forceinline__ void mma16816(float (&c)[4], uint32_t a0, uint32_t a2, uint32_t b0, uint32_t b1) {
  asm volatile("mma.sync.aligned.m16n8k16.row.col.f32.bf16.bf16.f32 {%0,%1,%2,%3}, {%4,%5,%6,%5}, {%7,%8}, {%0,%1,%2,%3};"
               : "+f"(c[0]), "+f"(c[1]), "+f"(c[2]), "+f"(c[3]) : "r"(a0), "r"(0u), "r"(a2), "r"(b0), "r"(b1));
}
__device__ __forceinline__ void ldsm4t(uint32_t (&r)[4], uint32_t addr) {
  asm volatile("ldmatrix.sync.aligned.m8n8.x4.trans.shared.b16 {%0,%1,%2,%3}, [%4];"
               : "=r"(r[0]), "=r"(r[1]), "=r"(r[2]), "=r"(r[3]) : "r"(addr) : "memory");
}

constexpr int MOE_BOX = 128 * 128;
constexpr int MOE_SLOTS = 6, MOE_SLOT = 2 * MOE_BOX;

__device__ __noinline__ void moe_ffn(uint8_t* smem, int e, const __nv_bfloat16* __restrict__ x, const CUtensorMap* m_gate,
                                     const CUtensorMap* m_up, const CUtensorMap* m_down) {
  const int tid = threadIdx.x, lane = tid & 31, warp = __shfl_sync(0xffffffffu, tid >> 5, 0), g = lane >> 2, t = lane & 3;
  const uint32_t ring = (s2u(smem) + 1023) & ~1023u, bfull = ring + MOE_SLOTS * MOE_SLOT, bempty = bfull + 8 * MOE_SLOTS;
  __nv_bfloat16* xs = reinterpret_cast<__nv_bfloat16*>(smem + (ring - s2u(smem)) + MOE_SLOTS * MOE_SLOT + 128);
  __nv_bfloat16* hs = xs + 2 * D_;
  const int nblk = e == 3 ? 6 : 7, nchunk = e == 3 ? 3 : 4;
  const int nst1 = nblk * 5, nst = nst1 + nchunk * 5;
  __shared__ float s_val[16];
  __shared__ int s_idx[16];
  __shared__ int s_top[2];
  __shared__ float s_gate[2];
  __shared__ unsigned s_last;
  if (tid == 0) {
    for (int i = 0; i < MOE_SLOTS; i++) { mbar_init(bfull + 8 * i, 1); mbar_init(bempty + 8 * i, 8); }
    asm volatile("fence.mbarrier_init.release.cluster;" ::: "memory");
  }
  reinterpret_cast<uint32_t*>(hs)[tid] = 0u;
  __syncthreads();
  if (warp == 8) {
    if (lane == 0) {
      pdl_wait();
      for (const long long t0 = clock64(); clock64() - t0 < 5000;) {}
      for (int st = 0; st < nst; st++) {
        const int sl = st % MOE_SLOTS;
        if (st >= MOE_SLOTS) mbar_wait(bempty + 8 * sl, ((st / MOE_SLOTS) - 1) & 1);
        const uint32_t slot = ring + sl * MOE_SLOT, bar = bfull + 8 * sl;
        mbar_expect_tx(bar, MOE_SLOT);
        if (st < nst1) {
          tma2d(slot, m_gate, (e * 7 + st / 5) * 64, (st % 5) * 128, bar);
          tma2d(slot + MOE_BOX, m_up, (e * 7 + st / 5) * 64, (st % 5) * 128, bar);
        } else {
          const int u = st - nst1;
          tma2d(slot, m_down, (u % 5) * 128, e * 448 + (u / 5) * 128, bar);
          tma2d(slot + MOE_BOX, m_down, (u % 5) * 128 + 64, e * 448 + (u / 5) * 128, bar);
        }
      }
    }
    __syncwarp();
  }

  if (warp < 8) {
    float rv[8];
    unsigned long long pk[8];
#pragma unroll
    for (int i = 0; i < 8; i++) pk[i] = ld_packet(&g_rp[tid + 256 * i]);
#pragma unroll
    for (int i = 0; i < 8; i++)
      rv[i] = __uint_as_float((uint32_t)(pk[i] >> 32) == tag ? (uint32_t)pk[i] : get_packet(&g_rp[tid + 256 * i], tag));
    int first = -1;
    for (int pass = 0; pass < 2; pass++) {
      float bv = -INFINITY; int bi = 0x7fffffff;
#pragma unroll
      for (int i = 0; i < 8; i++) {
        const int idx = tid + 256 * i;
        if (idx != first && (rv[i] > bv || (rv[i] == bv && idx < bi))) { bv = rv[i]; bi = idx; }
      }
#pragma unroll
      for (int o = 16; o; o >>= 1) {
        const float ov = __shfl_xor_sync(0xffffffffu, bv, o);
        const int oi = __shfl_xor_sync(0xffffffffu, bi, o);
        if (ov > bv || (ov == bv && oi < bi)) { bv = ov; bi = oi; }
      }
      if (lane == 0) { s_val[warp] = bv; s_idx[warp] = bi; }
      bar_sync(1, 256);
      if (warp == 0) {
        float v = s_val[lane & 7]; int ix = s_idx[lane & 7];
#pragma unroll
        for (int o = 4; o; o >>= 1) {
          const float ov = __shfl_xor_sync(0xffffffffu, v, o);
          const int oi = __shfl_xor_sync(0xffffffffu, ix, o);
          if (ov > v || (ov == v && oi < ix)) { v = ov; ix = oi; }
        }
        if (lane == 0) {
          if (ix < 0 || ix >= S_) ix = pass;
          s_top[pass] = ix;
          s_gate[pass] = bf_round(1.0f / (1.0f + __expf(-v)));
          if (e == 0) g_idx[pass] = ix;
        }
      }
      bar_sync(1, 256);
      first = s_top[0];
    }
    for (int i = tid; i < 2 * D_; i += 256) {
      const int tok = i / D_, d = i % D_;
      const uint32_t st = get_packet(&g_stat[s_top[tok]], tag);
      const float m = __uint_as_float(st & 0xFFFF0000u), rstd = __fdiv_rn(1.0f, __uint_as_float(st << 16));
      reinterpret_cast<uint16_t*>(xs)[i] =
          (uint16_t)(__float_as_uint(bf_round(bf_round(__bfloat162float(x[s_top[tok] * D_ + d]) - m) * rstd)) >> 16);
    }
    bar_sync(1, 256);

    const uint32_t* xs32 = reinterpret_cast<const uint32_t*>(xs);
    int st = 0;
#pragma unroll 1
    for (int blk = 0; blk < nblk; blk++) {
      float cg[4] = {0.f, 0.f, 0.f, 0.f}, cu[4] = {0.f, 0.f, 0.f, 0.f};
#pragma unroll 1
      for (int kc = 0; kc < 5; kc++, st++) {
        const int sl = st % MOE_SLOTS;
        mbar_wait(bfull + 8 * sl, (st / MOE_SLOTS) & 1);
        const uint32_t base = ring + sl * MOE_SLOT + (lane >> 4) * MOE_BOX + (lane & 15) * 128 + ((warp ^ (lane & 7)) << 4);
#pragma unroll
        for (int ks = 0; ks < 8; ks++) {
          const int kw = kc * 64 + ks * 8 + t;
          const uint32_t a0 = g < 2 ? xs32[g * (D_ / 2) + kw] : 0u, a2 = g < 2 ? xs32[g * (D_ / 2) + kw + 4] : 0u;
          uint32_t b[4];
          ldsm4t(b, base + ks * 2048);
          mma16816(cg, a0, a2, b[0], b[1]);
          mma16816(cu, a0, a2, b[2], b[3]);
        }
        __syncwarp();
        if (lane == 0) mbar_arrive(bempty + 8 * sl);
      }
      if (g < 2) {
        float h[2];
#pragma unroll
        for (int i = 0; i < 2; i++) {
          const float gb = bf_round(cg[i]), ub = bf_round(cu[i]);
          h[i] = bf_round(gb / (1.0f + __expf(-gb))) * ub;
        }
        reinterpret_cast<uint32_t*>(hs)[g * 256 + blk * 32 + warp * 4 + t] = pack_bf(h[0], h[1]);
      }
    }
    bar_sync(1, 256);

    float cd[5][2][4];
#pragma unroll
    for (int q = 0; q < 5; q++)
#pragma unroll
      for (int i = 0; i < 4; i++) { cd[q][0][i] = 0.f; cd[q][1][i] = 0.f; }
    const uint32_t* hs32 = reinterpret_cast<const uint32_t*>(hs);
#pragma unroll 1
    for (int fc = 0; fc < nchunk; fc++) {
#pragma unroll
      for (int q = 0; q < 5; q++, st++) {
        const int sl = st % MOE_SLOTS;
        mbar_wait(bfull + 8 * sl, (st / MOE_SLOTS) & 1);
        const uint32_t base = ring + sl * MOE_SLOT + (lane >> 4) * MOE_BOX + (lane & 15) * 128 + ((warp ^ (lane & 7)) << 4);
#pragma unroll
        for (int ks = 0; ks < 8; ks++) {
          const int kw = fc * 64 + ks * 8 + t;
          const uint32_t a0 = g < 2 ? hs32[g * 256 + kw] : 0u, a2 = g < 2 ? hs32[g * 256 + kw + 4] : 0u;
          uint32_t b[4];
          ldsm4t(b, base + ks * 2048);
          mma16816(cd[q][0], a0, a2, b[0], b[1]);
          mma16816(cd[q][1], a0, a2, b[2], b[3]);
        }
        __syncwarp();
        if (lane == 0) mbar_arrive(bempty + 8 * sl);
      }
    }
    if (g < 2) {
#pragma unroll
      for (int q = 0; q < 5; q++)
#pragma unroll
        for (int b = 0; b < 2; b++)
          *reinterpret_cast<float2*>(&g_ypart[(e * 2 + g) * D_ + q * 128 + b * 64 + warp * 8 + 2 * t]) =
              make_float2(cd[q][b][0], cd[q][b][1]);
    }
  }
  __threadfence();
  __syncthreads();
  if (tid == 0) s_last = atomicAdd(&g_ffn_done, 1u) & 3u;
  __syncthreads();
  if (s_last == 3) {
    __threadfence();
    for (int i = tid; i < D_; i += K2_THREADS) {
      const int tok = i / (D_ / 2), d = 2 * (i % (D_ / 2));
      float s0 = 0.f, s1 = 0.f;
#pragma unroll
      for (int k = 0; k < 4; k++) {
        const float2 v = __ldcg(reinterpret_cast<const float2*>(&g_ypart[(k * 2 + tok) * D_ + d]));
        s0 += v.x; s1 += v.y;
      }
      g_upd[i] = pack_bf(bf_round(s0) * s_gate[tok], bf_round(s1) * s_gate[tok]);
    }
  }
}

__device__ __forceinline__ void attn_fallback(float (&o)[12], uint8_t* smem, uint32_t sK, uint32_t sV, uint32_t qoff, int wg,
                                              uint64_t dQ0, uint64_t dQ1) {
  const int tid = threadIdx.x & 127;
  uint16_t* q16 = reinterpret_cast<uint16_t*>(smem + qoff);
  for (int i = tid; i < 8 * 192; i += 128) {
    const int in = i % 192, slot = (in >> 6) * 8 + (in & 7);
    uint16_t* p = q16 + i;
    const bool cst = slot == 14 || slot == 15 || slot == 22 || slot == 23;
    const float v = cst ? 0.f : __uint_as_float((uint32_t)*p << 16) * 2361183241434822606848.0f;
    *p = (uint16_t)(__float_as_uint(v) >> 16);
  }
  fence_async_smem();
  bar_sync(1 + wg, 128);
  const uint64_t dK0 = mkdesc(sK, 128, 384, 0), dK1 = mkdesc(sK + 256, 0, 384, 0), dV = mkdesc(sV, 384, 128, 0);
  const float up = 2361183241434822606848.0f, down = 4.235164736271502e-22f;
  float m0 = -INFINITY, m1 = -INFINITY;
#pragma unroll
  for (int i = 0; i < 12; i++) o[i] = 0.f;
#pragma unroll 1
  for (int j = 0; j < 32; j++) {
    float s[32];
    uint32_t p[16];
    const uint64_t off = (uint64_t)(j * 192);
    WG_FENCE();
    mma_ss64<0>(s, dQ0, dK0 + off);
    mma_ss64<1>(s, dQ1, dK1 + off);
    WG_COMMIT();
    wg_wait<0>();
    pin(s);
    pin(o);
    float n0 = m0, n1 = m1;
#pragma unroll
    for (int b = 0; b < 8; b++) {
      const float f = ((POLY_PAT >> b) & 1) ? up : down;
      s[4 * b] *= f; s[4 * b + 1] *= f; s[4 * b + 2] *= f; s[4 * b + 3] *= f;
      n0 = fmaxf(n0, fmaxf(s[4 * b], s[4 * b + 1]));
      n1 = fmaxf(n1, fmaxf(s[4 * b + 2], s[4 * b + 3]));
    }
    n0 = fmaxf(n0, __shfl_xor_sync(0xffffffffu, n0, 1)); n0 = fmaxf(n0, __shfl_xor_sync(0xffffffffu, n0, 2));
    n1 = fmaxf(n1, __shfl_xor_sync(0xffffffffu, n1, 1)); n1 = fmaxf(n1, __shfl_xor_sync(0xffffffffu, n1, 2));
    const float c0 = exp2f(m0 - n0), c1 = exp2f(m1 - n1);
    m0 = n0; m1 = n1;
#pragma unroll
    for (int b = 0; b < 3; b++) { o[4 * b] *= c0; o[4 * b + 1] *= c0; o[4 * b + 2] *= c1; o[4 * b + 3] *= c1; }
#pragma unroll
    for (int b = 0; b < 8; b++) {
      p[2 * b] = exp_mufu(s[4 * b] - m0, s[4 * b + 1] - m0);
      p[2 * b + 1] = exp_mufu(s[4 * b + 2] - m1, s[4 * b + 3] - m1);
    }
    pin(o);
    pin(p);
    WG_FENCE();
#pragma unroll
    for (int k = 0; k < 4; k++) mma_pv(o, p[4 * k], p[4 * k + 1], p[4 * k + 2], p[4 * k + 3], dV + off + 48 * k);
    WG_COMMIT();
    wg_wait<0>();
    pin(o);
  }
}

__device__ __forceinline__ float2 store_shift(const float (&s)[32], uint8_t* qtile) {
  const int lane = threadIdx.x & 31, warp4 = (threadIdx.x >> 5) & 3, g = lane >> 2, t = lane & 3;
  float m0 = -INFINITY, m1 = -INFINITY, p0 = -INFINITY, p1 = -INFINITY;
#pragma unroll
  for (int b = 0; b < 8; b++) {
    if (!((POLY_PAT >> b) & 1)) {
      m0 = fmaxf(m0, fmaxf(s[4 * b], s[4 * b + 1]));
      m1 = fmaxf(m1, fmaxf(s[4 * b + 2], s[4 * b + 3]));
    } else {
      p0 = fmaxf(p0, fmaxf(s[4 * b], s[4 * b + 1]));
      p1 = fmaxf(p1, fmaxf(s[4 * b + 2], s[4 * b + 3]));
    }
  }
  const float k = 2361183241434822606848.0f;
  m0 = fmaxf(m0, p0 * k * k - 127.0f);
  m1 = fmaxf(m1, p1 * k * k - 127.0f);
  m0 = fmaxf(m0, __shfl_xor_sync(0xffffffffu, m0, 1)); m1 = fmaxf(m1, __shfl_xor_sync(0xffffffffu, m1, 1));
  m0 = fmaxf(m0, __shfl_xor_sync(0xffffffffu, m0, 2)); m1 = fmaxf(m1, __shfl_xor_sync(0xffffffffu, m1, 2));
  const float c0 = bf_round(m0 + 90.0f), c1 = bf_round(m1 + 90.0f);
  if (t == 0) {
    uint8_t* qp = qtile + (warp4 * 2) * 384 + 256 + g * 16 + 12;
    *reinterpret_cast<uint16_t*>(qp) = (uint16_t)(__float_as_uint(c0 * -5.421010862427522e-20f) >> 16);
    *reinterpret_cast<uint16_t*>(qp + 384) = (uint16_t)(__float_as_uint(c1 * -5.421010862427522e-20f) >> 16);
  }
  return make_float2(c0, c1);
}

__device__ __forceinline__ bool store_output(const float (&o)[12], __nv_bfloat16* __restrict__ orow) {
  const int lane = threadIdx.x & 31, warp4 = (threadIdx.x >> 5) & 3, g = lane >> 2, t = lane & 3;
  const float l0 = __shfl_sync(0xffffffffu, o[8], (lane & ~3) | 2);
  const float l1 = __shfl_sync(0xffffffffu, o[10], (lane & ~3) | 2);
  float i0, i1;
  asm("rcp.approx.ftz.f32 %0, %1;" : "=f"(i0) : "f"(l0));
  asm("rcp.approx.ftz.f32 %0, %1;" : "=f"(i1) : "f"(l1));
  uint32_t* dst0 = reinterpret_cast<uint32_t*>(orow + (warp4 * 16 + g) * D_) + t;
  uint32_t* dst1 = dst0 + 8 * (D_ / 2);
  dst0[0] = pack_bf(o[0] * i0, o[1] * i0);  dst1[0] = pack_bf(o[2] * i1, o[3] * i1);
  dst0[4] = pack_bf(o[4] * i0, o[5] * i0);  dst1[4] = pack_bf(o[6] * i1, o[7] * i1);
  if (t < 2) { dst0[8] = pack_bf(o[8] * i0, o[9] * i0); dst1[8] = pack_bf(o[10] * i1, o[11] * i1); }
  bool ok = l0 >= 7.888609052210118e-31f && l0 <= 1.0e37f && l1 >= 7.888609052210118e-31f && l1 <= 1.0e37f;
#pragma unroll
  for (int i = 0; i < 12; i++) ok = ok && fabsf(o[i]) <= 3.0e38f;
  return ok;
}

__global__ void __launch_bounds__(K2_THREADS, 1)
k2_attn(const __grid_constant__ CUtensorMap m_gate, const __grid_constant__ CUtensorMap m_up,
        const __grid_constant__ CUtensorMap m_down, const __nv_bfloat16* __restrict__ x) {
  extern __shared__ __align__(128) uint8_t smem[];
  const int tid = threadIdx.x;
  if (blockIdx.x < 4) {
    pdl_launch();
    moe_ffn(smem, blockIdx.x, x, &m_gate, &m_up, &m_down);
    return;
  }
  const int id = blockIdx.x - 4, head = id >> 2, qb = id & 3;
  const uint32_t sK = s2u(smem), sV = sK + K2_KV_BYTES, sQall = sV + K2_KV_BYTES, sZero = sQall + K2_Q_BYTES;
  const uint32_t bars = sZero + K2_ZERO_BYTES;
  if (tid == 0) {
    for (int i = 0; i < 6; i++) mbar_init(bars + 8 * i, 1);
    asm volatile("fence.mbarrier_init.release.cluster;" ::: "memory");
  }
  if (tid < K2_ZERO_BYTES / 16) reinterpret_cast<uint4*>(smem + 2 * K2_KV_BYTES + K2_Q_BYTES)[tid] = make_uint4(0, 0, 0, 0);
  fence_async_smem();
  __syncthreads();
  pdl_wait();
  pdl_launch();
  if (tid >= 497) g_cs[id * 15 + (tid - 497)] = 0ull;
  if (tid == 0) {
    const uint8_t* gq = reinterpret_cast<const uint8_t*>(g_qkv) + (size_t)head * HEAD_BYTES + qb * K2_Q_BYTES;
    const uint8_t* gk = reinterpret_cast<const uint8_t*>(g_qkv) + (size_t)(H_ + head) * HEAD_BYTES;
    const uint8_t* gv = gk + (size_t)H_ * HEAD_BYTES;
    mbar_expect_tx(bars + 40, K2_Q_BYTES + 6144);
    bulk_g2s(sK, gk, 6144, bars + 40);
    bulk_g2s(sQall, gq, K2_Q_BYTES, bars + 40);
    mbar_expect_tx(bars, 6144);
    bulk_g2s(sV, gv, 6144, bars);
    for (int c = 1; c < 5; c++) {
      const uint32_t off = 6144u << (c - 1), bytes = off;
      mbar_expect_tx(bars + 8 * c, 2 * bytes);
      bulk_g2s(sK + off, gk + off, bytes, bars + 8 * c);
      bulk_g2s(sV + off, gv + off, bytes, bars + 8 * c);
    }
  }
  const int wg = __reduce_max_sync(0xffffffffu, tid >> 7);
  __nv_bfloat16* orow = g_o + (qb * 512 + wg * 64) * D_ + head * 20;
  const uint64_t dK0 = mkdesc(sK, 128, 384, 0), dK1 = mkdesc(sK + 256, 0, 384, 0), dV = mkdesc(sV, 384, 128, 0);
  const uint32_t qoffA = 2 * K2_KV_BYTES + wg * 3072, qoffB = qoffA + 4 * 3072;
  const uint64_t dQA0 = mkdesc(sK + qoffA, 128, 384, 0), dQA1 = mkdesc(sK + qoffA + 256, sZero - (sK + qoffA + 256), 384, 0);
  const uint64_t dQB0 = mkdesc(sK + qoffB, 128, 384, 0), dQB1 = mkdesc(sK + qoffB + 256, sZero - (sK + qoffB + 256), 384, 0);
  float o[12];
  float s0[32], s1[32];
  uint32_t pa[8], pb[8];

#define QK(Sreg, Q0, Q1, OFF) do { mma_ss64<0>(Sreg, Q0, dK0 + (OFF)); mma_ss64<1>(Sreg, Q1, dK1 + (OFF)); } while (0)
#define PV(P, I, OFF) mma_pv(o, P[4 * (I)], P[4 * (I) + 1], P[4 * (I) + 2], P[4 * (I) + 3], dV + (OFF))
#define HALF_STEP(SA, SB, Q0, Q1, OFFP, OFFN)                               \
  WG_FENCE(); QK(SB, Q0, Q1, OFFN); WG_COMMIT();                            \
  exp_half<0>(SA, pa);                                                      \
  WG_FENCE(); PV(pa, 0, OFFP); PV(pa, 1, (OFFP) + 48); WG_COMMIT();         \
  wg_wait<2>();                                                             \
  exp_half<4>(SA, pb);                                                      \
  WG_FENCE(); PV(pb, 0, (OFFP) + 96); PV(pb, 1, (OFFP) + 144); WG_COMMIT(); \
  wg_wait<1>();                                                             \
  pin(SB);
#define LAST_STEPS(Q0, Q1)                                                  \
  {                                                                         \
    const uint64_t off = (uint64_t)(15 * 384);                              \
    HALF_STEP(s0, s1, Q0, Q1, off, off + 192)                               \
    exp_half<0>(s1, pa);                                                    \
    WG_FENCE(); PV(pa, 0, off + 192); PV(pa, 1, off + 240); WG_COMMIT();    \
    wg_wait<1>();                                                           \
    exp_half<4>(s1, pb);                                                    \
    WG_FENCE(); PV(pb, 0, off + 288); PV(pb, 1, off + 336); WG_COMMIT();    \
  }

  mbar_wait(bars + 40, 0);
  WG_FENCE(); QK(s0, dQA0, dQA1, 0); QK(s1, dQB0, dQB1, 0); WG_COMMIT();
  wg_wait<0>(); pin(s0); pin(s1);
  {
    const float2 c = store_shift(s0, smem + qoffA);
    store_shift(s1, smem + qoffB);
    fence_async_smem();
    const float k = 4.235164736271502e-22f;
    const float d0 = c.x * k * k, d1 = c.y * k * k;
#pragma unroll
    for (int b = 0; b < 8; b++) {
      const bool poly = (POLY_PAT >> b) & 1;
      s0[4 * b] -= poly ? d0 : c.x; s0[4 * b + 1] -= poly ? d0 : c.x;
      s0[4 * b + 2] -= poly ? d1 : c.y; s0[4 * b + 3] -= poly ? d1 : c.y;
    }
#pragma unroll
    for (int i = 0; i < 12; i++) o[i] = 0.f;
    pin(o);
    pin(s0);
    bar_sync(1 + wg, 128);
  }

  mbar_wait(bars, 0);
#pragma unroll 1
  for (int i = 0; i < 15; i++) {
    const uint64_t off = (uint64_t)(i * 384);
    const int in = i + 1;
    if ((in & (in - 1)) == 0) mbar_wait(bars + 8 * (32 - __clz(in)), 0);
    HALF_STEP(s0, s1, dQA0, dQA1, off, off + 192)
    HALF_STEP(s1, s0, dQA0, dQA1, off + 192, off + 384)
  }
  LAST_STEPS(dQA0, dQA1)
  WG_FENCE(); QK(s0, dQB0, dQB1, 0); WG_COMMIT();
  wg_wait<1>();
  pin(o);
  const bool okA = store_output(o, orow);

#pragma unroll
  for (int i = 0; i < 12; i++) o[i] = 0.f;
  pin(o);
  wg_wait<0>();
  pin(s0);
#pragma unroll 1
  for (int i = 0; i < 15; i++) {
    const uint64_t off = (uint64_t)(i * 384);
    HALF_STEP(s0, s1, dQB0, dQB1, off, off + 192)
    HALF_STEP(s1, s0, dQB0, dQB1, off + 192, off + 384)
  }
  LAST_STEPS(dQB0, dQB1)
  wg_wait<0>();
  pin(o);
  const bool okB = store_output(o, orow + 256 * D_);

  uint32_t bad;
  asm volatile("{\n.reg .pred p, q;\nsetp.eq.u32 p, %1, 0;\nbar.red.or.pred q, %2, 128, p;\nselp.u32 %0, 1, 0, q;\n}"
               : "=r"(bad) : "r"((uint32_t)(okA && okB)), "r"(1 + wg) : "memory");
  if (bad) {
#pragma unroll 1
    for (int task = 0; task < 2; task++) {
      attn_fallback(o, smem, sK, sV, task ? qoffB : qoffA, wg, task ? dQB0 : dQA0, task ? dQB1 : dQA1);
      store_output(o, orow + task * 256 * D_);
    }
  }
#undef QK
#undef PV
#undef HALF_STEP
#undef LAST_STEPS
}

constexpr int K3_THREADS = 288;
constexpr int K3_STAGES = 7;
constexpr int K3_B_BYTES = 80 * 640 * 2, K3_A_BYTES = 128 * 64 * 2;
constexpr int K3_SMEM = K3_STAGES * K3_A_BYTES + K3_B_BYTES + 1024 + 256;

__global__ void __launch_bounds__(K3_THREADS, 1)
k3_out(const __grid_constant__ CUtensorMap map_o, const __grid_constant__ CUtensorMap map_out,
       const __nv_bfloat16* __restrict__ x) {
  extern __shared__ uint8_t smem_raw[];
  const int tid = threadIdx.x, warp = __shfl_sync(0xffffffffu, tid >> 5, 0), lane = tid & 31;
  uint8_t* smem = smem_raw + (((s2u(smem_raw) + 1023) & ~1023u) - s2u(smem_raw));
  const uint32_t sbase = s2u(smem);
  const uint32_t sB = sbase + K3_STAGES * K3_A_BYTES;
  const uint32_t bar_full = sB + K3_B_BYTES, bar_empty = bar_full + 8 * K3_STAGES, bar_b = bar_empty + 8 * K3_STAGES;
  const int mb = blockIdx.x >> 3, nb = blockIdx.x & 7;
  if (warp == 8) {
    if (lane == 0) {
      asm volatile("prefetch.tensormap [%0];" ::"l"(&map_o) : "memory");
      asm volatile("prefetch.tensormap [%0];" ::"l"(&map_out) : "memory");
      for (int s = 0; s < K3_STAGES; s++) { mbar_init(bar_full + 8 * s, 1); mbar_init(bar_empty + 8 * s, 2); }
      mbar_init(bar_b, 1);
      asm volatile("fence.mbarrier_init.release.cluster;" ::: "memory");
    }
    __syncthreads();
    if (lane == 0) {
      mbar_expect_tx(bar_b, K3_B_BYTES);
      bulk_g2s(sB, reinterpret_cast<const uint8_t*>(g_wot) + (size_t)nb * K3_B_BYTES, K3_B_BYTES, bar_b);
      pdl_wait();
      for (int kc = 0; kc < 10; kc++) {
        const int s = kc % K3_STAGES;
        if (kc >= K3_STAGES) mbar_wait(bar_empty + 8 * s, 0);
        mbar_expect_tx(bar_full + 8 * s, K3_A_BYTES);
        tma2d(sbase + s * K3_A_BYTES, &map_o, kc * 64, mb * 128, bar_full + 8 * s);
      }

    }
    return;
  }
  const int wg = warp >> 2, g = lane >> 2, t = lane & 3;
  const int row = mb * 128 + wg * 64 + (warp & 3) * 16 + g;
  const int col = nb * 80 + 2 * t;
  uint32_t xr[20];
  float2 sp0 = make_float2(0.f, 1.f), sp1 = sp0;
#pragma unroll
  for (int j = 0; j < 20; j++) xr[j] = 0u;
  __syncthreads();
  float acc[40];
#pragma unroll
  for (int i = 0; i < 40; i++) acc[i] = 0.f;
  int i0 = -1, i1 = -1;
#pragma unroll 1
  for (int trip = 0; trip < 2; trip++) {
    const bool real = trip != 0;
    if (real) {
      sp0 = __ldcg(&g_statp[row]); sp1 = __ldcg(&g_statp[row + 8]);
#pragma unroll
      for (int j = 0; j < 10; j++) {
        xr[2 * j] = __ldg(reinterpret_cast<const uint32_t*>(x + row * D_ + col + 8 * j));
        xr[2 * j + 1] = __ldg(reinterpret_cast<const uint32_t*>(x + (row + 8) * D_ + col + 8 * j));
      }
      pdl_wait();
      if (tid < 16) { g_rp[blockIdx.x * 16 + tid] = 0ull; g_stat[blockIdx.x * 16 + tid] = 0ull; }
      i0 = __ldcg(&g_idx[0]); i1 = __ldcg(&g_idx[1]);
      mbar_wait(bar_b, 0);
#pragma unroll 1
      for (int kc = 0; kc < 10; kc++) {
        const int s = kc % K3_STAGES;
        mbar_wait(bar_full + 8 * s, (kc / K3_STAGES) & 1);
        const uint64_t da = mkdesc(sbase + s * K3_A_BYTES + wg * 8192, 16, 1024, 1);
        const uint64_t db = mkdesc(sB + kc * 10240, 128, 1024, 0);
        WG_FENCE();
#pragma unroll
        for (int kk = 0; kk < 4; kk++) mma_ss80(acc, da + kk * 2, db + kk * 16, (kc | kk) != 0);
        WG_COMMIT();
        if (kc > 0) {
          wg_wait<1>();
          if ((tid & 127) == 0 && kc - 1 < 10 - K3_STAGES) mbar_arrive(bar_empty + 8 * (kc - 1));
        }
      }
      wg_wait<0>();
      pin(acc);
      bar_sync(1, 256);
    }
    const uint32_t stg = sB + ((wg * 64 + (warp & 3) * 16 + g) * 40 + t) * 4;
#pragma unroll
    for (int h = 0; h < 2; h++) {
      const float2 sp = h ? sp1 : sp0;
      const uint32_t m2 = pack_bf(sp.x, sp.x);
      uint32_t n[10];
#pragma unroll
      for (int j = 0; j < 10; j++) {
        const uint32_t d = bf2_sub(xr[2 * j + h], m2);
        n[j] = pack_bf(bf_lo(d) * sp.y, bf_hi(d) * sp.y);
      }
      const int r = row + 8 * h;
      if (r == i0 || r == i1) {
        const uint32_t* up = g_upd + (r == i0 ? 0 : D_ / 2) + (col >> 1);
#pragma unroll
        for (int j = 0; j < 10; j++) n[j] = bf2_add(n[j], __ldcg(up + 4 * j));
      }
#pragma unroll
      for (int j = 0; j < 10; j++) {
        const uint32_t a = bf2_add(xr[2 * j + h], pack_bf(acc[4 * j + 2 * h], acc[4 * j + 2 * h + 1]));
        sts_if(real, stg + (h * 320 + 4 * j) * 4, bf2_add(a, n[j]));
      }
    }
  }
  fence_async_smem();
  bar_sync(2 + wg, 128);
  if ((tid & 127) == 0) {
    asm volatile("cp.async.bulk.tensor.2d.global.shared::cta.bulk_group [%0, {%2, %3}], [%1];"
                 ::"l"(&map_out), "r"(sB + wg * 64 * 160), "r"(nb * 80), "r"(mb * 128 + wg * 64) : "memory");
    asm volatile("cp.async.bulk.commit_group;" ::: "memory");
    asm volatile("cp.async.bulk.wait_group.read 0;" ::: "memory");
  }
}

typedef CUresult (*EncodeFn)(CUtensorMap*, CUtensorMapDataType, cuuint32_t, void*, const cuuint64_t*, const cuuint64_t*,
                             const cuuint32_t*, const cuuint32_t*, CUtensorMapInterleave, CUtensorMapSwizzle,
                             CUtensorMapL2promotion, CUtensorMapFloatOOBfill);

CUtensorMap make_map_w(EncodeFn fn, const void* ptr, uint32_t nblk) {
  CUtensorMap m;
  const cuuint64_t dims[3] = {3 * D_, D_, nblk};
  const cuuint64_t strides[2] = {3 * D_ * 2, 128};
  const cuuint32_t box[3] = {64, 64, nblk};
  const cuuint32_t es[3] = {1, 1, 1};
  fn(&m, CU_TENSOR_MAP_DATA_TYPE_BFLOAT16, 3, const_cast<void*>(ptr), dims, strides, box, es, CU_TENSOR_MAP_INTERLEAVE_NONE,
     CU_TENSOR_MAP_SWIZZLE_128B, CU_TENSOR_MAP_L2_PROMOTION_L2_128B, CU_TENSOR_MAP_FLOAT_OOB_FILL_NONE);
  return m;
}

CUtensorMap make_map(EncodeFn fn, const void* ptr, uint64_t cols, uint64_t rows, uint32_t box_cols, uint32_t box_rows,
                     CUtensorMapSwizzle swz) {
  CUtensorMap m;
  const cuuint64_t dims[2] = {cols, rows};
  const cuuint64_t strides[1] = {cols * 2};
  const cuuint32_t box[2] = {box_cols, box_rows};
  const cuuint32_t es[2] = {1, 1};
  fn(&m, CU_TENSOR_MAP_DATA_TYPE_BFLOAT16, 2, const_cast<void*>(ptr), dims, strides, box, es, CU_TENSOR_MAP_INTERLEAVE_NONE,
     swz, CU_TENSOR_MAP_L2_PROMOTION_L2_128B, CU_TENSOR_MAP_FLOAT_OOB_FILL_NONE);
  return m;
}

}

extern "C" void kernel_launch(void* const* d_in, const int* in_sizes, int n_in, void* d_out, int out_size) {
  (void)in_sizes; (void)n_in; (void)out_size;
  const __nv_bfloat16* x = (const __nv_bfloat16*)d_in[0];
  const __nv_bfloat16* wqkv = (const __nv_bfloat16*)d_in[1];
  const __nv_bfloat16* wo = (const __nv_bfloat16*)d_in[2];
  const __nv_bfloat16* w_r = (const __nv_bfloat16*)d_in[4];
  const __nv_bfloat16* w_gate = (const __nv_bfloat16*)d_in[5];
  const __nv_bfloat16* w_up = (const __nv_bfloat16*)d_in[6];
  const __nv_bfloat16* w_down = (const __nv_bfloat16*)d_in[7];

  static EncodeFn encode = nullptr;
  static void* p_o = nullptr;
  if (!encode) {
    void* fn = nullptr;
    cudaDriverEntryPointQueryResult qr;
    cudaGetDriverEntryPoint("cuTensorMapEncodeTiled", &fn, cudaEnableDefault, &qr);
    encode = (EncodeFn)fn;
    cudaGetSymbolAddress(&p_o, g_o);
    cudaFuncSetAttribute(k1_ln_qkv, cudaFuncAttributeMaxDynamicSharedMemorySize, K1_SMEM);
    cudaFuncSetAttribute(k2_attn, cudaFuncAttributeMaxDynamicSharedMemorySize, K2_SMEM);
    cudaFuncSetAttribute(k3_out, cudaFuncAttributeMaxDynamicSharedMemorySize, K3_SMEM);
  }
  const CUtensorMap map_x = make_map(encode, x, D_, S_, 64, 128, CU_TENSOR_MAP_SWIZZLE_128B);
  const CUtensorMap map_w = make_map(encode, wqkv, 3 * D_, D_, 64, 64, CU_TENSOR_MAP_SWIZZLE_128B);
  const CUtensorMap map_w4 = make_map_w(encode, wqkv, 4), map_w3 = make_map_w(encode, wqkv, 3);
  const CUtensorMap map_o = make_map(encode, p_o, D_, S_, 64, 128, CU_TENSOR_MAP_SWIZZLE_128B);
  const CUtensorMap map_gate = make_map(encode, w_gate, F_, D_, 64, 128, CU_TENSOR_MAP_SWIZZLE_128B);
  const CUtensorMap map_up = make_map(encode, w_up, F_, D_, 64, 128, CU_TENSOR_MAP_SWIZZLE_128B);
  const CUtensorMap map_down = make_map(encode, w_down, D_, F_, 64, 128, CU_TENSOR_MAP_SWIZZLE_128B);
  const CUtensorMap map_out = make_map(encode, d_out, D_, S_, 80, 64, CU_TENSOR_MAP_SWIZZLE_NONE);

  cudaStream_t st = cudaStreamPerThread;
  k1_ln_qkv<<<128, K1_THREADS, K1_SMEM, st>>>(map_x, map_w, map_w4, map_w3, x, wqkv, w_r, wo);

  cudaLaunchAttribute at[1];
  at[0].id = cudaLaunchAttributeProgrammaticStreamSerialization;
  at[0].val.programmaticStreamSerializationAllowed = 1;
  cudaLaunchConfig_t cfg = {};
  cfg.stream = st;
  cfg.attrs = at;
  cfg.numAttrs = 1;
  cfg.gridDim = dim3(132); cfg.blockDim = dim3(K2_THREADS); cfg.dynamicSmemBytes = K2_SMEM;
  cudaLaunchKernelEx(&cfg, k2_attn, map_gate, map_up, map_down, x);
  cfg.gridDim = dim3(128); cfg.blockDim = dim3(K3_THREADS); cfg.dynamicSmemBytes = K3_SMEM;
  cudaLaunchKernelEx(&cfg, k3_out, map_o, map_out, x);
}
```
